```python
import torch

def _softmax(x, axis=-1):
    return torch.softmax(x, dim=axis)

def _gelu(x):
    return torch.nn.functional.gelu(x, approximate='tanh')

def _silu(x):
    return torch.nn.functional.silu(x)

def _sigmoid(x):
    return torch.sigmoid(x)

def _layernorm(x, axis=-1, eps=1e-05):
    m = x.mean(dim=axis, keepdim=True)
    v = x.var(dim=axis, keepdim=True, unbiased=False)
    return (x - m) / torch.sqrt(v + eps)

def _scatter_add(tgt, idx, src, axis=0):
    return tgt.clone().index_add_(axis, idx, src)

def _segment_sum(src, seg, n):
    out = torch.zeros((n,) + src.shape[1:], dtype=src.dtype)
    return out.index_add_(0, seg, src)

def _pad(x, pw):
    flat = tuple((v for pair in reversed(pw) for v in pair))
    return torch.nn.functional.pad(x, flat)
kernel_name = 'standalone__kv_cache_quant_pre_rope_vs_post_rope__sampling'

def setup_inputs():

    _w = lambda a: (lambda t: t.to(torch.bfloat16) if t.is_floating_point() else t)(torch.as_tensor(a))
    B, Sq, Skv = (8, 1, 2048)
    H, Dh0 = (32, 192)
    G = -1 if -1 > 0 else Dh0
    G = max(2, G // 2 * 2)
    Dh = max(G, Dh0 // G * G)
    Skv = max(Skv, Sq)
    ng = Dh // G
    bits = 4 if 4 > 1 else 4
    bits = max(2, min(8, bits))
    qmax = (1 << bits) - 1
    half = Dh // 2
    inv = 1.0 / 10000.0 ** (torch.arange(half) / max(1, half))
    ang_k = torch.arange(Skv)[:, None] * inv[None, :]
    ang_q = torch.arange(Skv - Sq, Skv)[:, None] * inv[None, :]
    kc = torch.cat([torch.cos(ang_k), torch.cos(ang_k)], dim=-1)
    ks = torch.cat([torch.sin(ang_k), torch.sin(ang_k)], dim=-1)
    qc = torch.cat([torch.cos(ang_q), torch.cos(ang_q)], dim=-1)
    qs = torch.cat([torch.sin(ang_q), torch.sin(ang_q)], dim=-1)
    qk_i = torch.randint(0, qmax + 1, (B, H, Skv, Dh)).to(torch.int32)
    qv_i = torch.randint(0, qmax + 1, (B, H, Skv, Dh)).to(torch.int32)
    ksc = torch.abs((lambda *s: torch.randn(*s, dtype=torch.bfloat16) * 0.2)(B, H, Skv, ng)) * 0.1 + 0.01
    kzp = torch.full((B, H, Skv, ng), qmax / 2.0)
    vsc = torch.abs((lambda *s: torch.randn(*s, dtype=torch.bfloat16) * 0.2)(B, H, Skv, ng)) * 0.1 + 0.01
    vzp = torch.full((B, H, Skv, ng), qmax / 2.0)
    return {'q': _w((lambda *s: torch.randn(*s, dtype=torch.bfloat16) * 6.4)(B, H, Sq, Dh) * 0.5), 'qk': _w(qk_i), 'k_scales': _w(ksc), 'k_zeros': _w(kzp), 'qv': _w(qv_i), 'v_scales': _w(vsc), 'v_zeros': _w(vzp), 'q_cos': _w(qc), 'q_sin': _w(qs), 'k_cos': _w(kc), 'k_sin': _w(ks)}

def reference(q, qk, k_scales, k_zeros, qv, v_scales, v_zeros, q_cos, q_sin, k_cos, k_sin):
    B, H, Sq, Dh = q.shape
    ng = k_scales.shape[-1]
    G = Dh // ng
    half = Dh // 2
    ks = (lambda x, n, axis: torch.repeat_interleave(x, n, dim=axis))(k_scales, G, axis=-1)
    kz = (lambda x, n, axis: torch.repeat_interleave(x, n, dim=axis))(k_zeros, G, axis=-1)
    k = ((lambda x, dt: x.to(dt))(qk, q.dtype) - kz) * ks
    vs = (lambda x, n, axis: torch.repeat_interleave(x, n, dim=axis))(v_scales, G, axis=-1)
    vz = (lambda x, n, axis: torch.repeat_interleave(x, n, dim=axis))(v_zeros, G, axis=-1)
    v = ((lambda x, dt: x.to(dt))(qv, q.dtype) - vz) * vs
    k1 = k[..., :half].clone()
    k2 = k[..., half:].clone()
    krh = torch.concatenate([-k2, k1], axis=-1)
    kr = k * k_cos[None, None, :, :] + krh * k_sin[None, None, :, :]
    q1 = q[..., :half].clone()
    q2 = q[..., half:].clone()
    qrh = torch.concatenate([-q2, q1], axis=-1)
    qr = q * q_cos[None, None, :, :] + qrh * q_sin[None, None, :, :]
    logits = torch.einsum('bhqd,bhkd->bhqk', qr, kr) * float(Dh) ** (-0.5)
    attn = _softmax(logits, axis=-1)
    out = torch.einsum('bhqk,bhkd->bhqd', attn, v)
    return out
```

```cpp
#include <cuda_runtime.h>
#include <cuda.h>
#include <cuda_bf16.h>
#include <stdint.h>

namespace {

constexpr int kB = 8, kH = 32, kS = 2048, kD = 192;
constexpr int kNH = kB * kH;
constexpr int kTeams = 4;
constexpr int kSlots = 32;
constexpr int kRows = kS / kSlots;
constexpr int kRounds = kNH / kTeams;
constexpr int kStream = kTeams * kSlots;
constexpr int kGrid = kStream + kTeams;
constexpr int kCW = 16;
constexpr int kR = kRows / kCW;
constexpr int kThreads = (kCW + 2) * 32;
constexpr int kRowBytes = kD * 4;
constexpr int kChunk = kRows * kRowBytes;
constexpr int kNS = 3;
constexpr int kLead = 232;
constexpr int kLead3 = 300;
constexpr int kSleep = 200;
constexpr int kPR = 12;
constexpr int kScStride = 196;
constexpr int kOffScal = kNS * kChunk;
constexpr int kOffQ = kOffScal + kRounds * 4 * kRows * 2;
constexpr int kOffSc = kOffQ + kRounds * kD * 2;
constexpr int kOffBar = kOffSc + 2 * kCW * kScStride * 4;
constexpr int kF = 3;
constexpr int kFG = 4;
constexpr int kFW = kD / kFG;
constexpr int kFRows = kRows * kFG;
constexpr int kFHeads = kSlots / kFG;
constexpr int kDef0 = 16;
constexpr int kEarly = 4;
constexpr int kFBoxes = 16;
constexpr int kPrep = 40;
constexpr int kOffW = kOffScal;
constexpr int kOffFin = kOffW + kF * kFRows * 4;
constexpr int kPartStride = 20;
constexpr int kOffPart = kOffFin + kFW * 4;
constexpr int kOffMisc = kOffBar + (2 * kNS + 6 + kF * kFBoxes) * 8;
constexpr int kOffMax = kOffMisc + 16;
constexpr int kSmemBytes = kOffMax + 4 * kCW * 4;
constexpr int kRecWords = 112;
constexpr int kMG = 6;
static_assert(kNS >= 3, "ring");
static_assert(kOffBar % 8 == 0 && kOffSc % 16 == 0 && kOffMax % 16 == 0, "alignment");
static_assert(kPR % kMG == 0, "ring");
static_assert(kSmemBytes <= 232448, "smem");
static_assert(kDef0 + kFHeads < kPrep && kPrep + 3 < kRounds && kOffPart <= kOffScal + (kPrep - 2) * 4 * kRows * 2 &&
              kOffPart + kF * kFW * kPartStride * 4 <= kOffScal + (kRounds - 2) * 4 * kRows * 2 && kF <= kNS && kFBoxes == kCW, "deferred rounds");

__device__ __align__(128) unsigned long long g_rec[kPR * kStream * kRecWords];
__device__ __align__(128) unsigned long long g_pre[kTeams * kFHeads * kRecWords];
__device__ __align__(128) unsigned long long g_lg[kTeams * kFHeads * kF * kFRows];
__device__ __align__(128) unsigned int g_prog;
__device__ __align__(128) unsigned int g_epoch;
__device__ __align__(128) unsigned int g_arrive;
__device__ __align__(128) unsigned int g_mdone[kTeams * kMG * 32];

constexpr int kSpin = 1 << 24;

__device__ __forceinline__ uint32_t s2u(const void* p) { return (uint32_t)__cvta_generic_to_shared(p); }
__device__ __forceinline__ void mbar_init(uint32_t a, int c) {
    asm volatile("mbarrier.init.shared::cta.b64 [%0], %1;" ::"r"(a), "r"(c));
}
__device__ __forceinline__ void mbar_wait(uint32_t a, uint32_t ph) {
    uint32_t ok;
    for (int it = 0;; it++) {
        asm volatile(
            "{\n.reg .pred p;\nmbarrier.try_wait.parity.shared::cta.b64 p, [%1], %2;\nselp.u32 %0, 1, 0, p;\n}"
            : "=r"(ok) : "r"(a), "r"(ph) : "memory");
        if (ok) break;
        if (it > kSpin) __trap();
    }
}
__device__ __forceinline__ void mbar_arrive(uint32_t a) {
    asm volatile("mbarrier.arrive.shared::cta.b64 _, [%0];" ::"r"(a) : "memory");
}
__device__ __forceinline__ void mbar_expect(uint32_t a, uint32_t bytes) {
    asm volatile("mbarrier.arrive.expect_tx.shared::cta.b64 _, [%0], %1;" ::"r"(a), "r"(bytes) : "memory");
}
__device__ __forceinline__ void bulk_g2s_stream(uint32_t dst, const void* src, uint32_t bytes, uint32_t mbar, uint64_t pol) {
    asm volatile("cp.async.bulk.shared::cluster.global.mbarrier::complete_tx::bytes.L2::cache_hint [%0], [%1], %2, [%3], %4;"
                 ::"r"(dst), "l"(src), "r"(bytes), "r"(mbar), "l"(pol) : "memory");
}
__device__ __forceinline__ void bulk_g2s(uint32_t dst, const void* src, uint32_t bytes, uint32_t mbar) {
    asm volatile("cp.async.bulk.shared::cluster.global.mbarrier::complete_tx::bytes [%0], [%1], %2, [%3];"
                 ::"r"(dst), "l"(src), "r"(bytes), "r"(mbar) : "memory");
}
__device__ __forceinline__ void cp16(uint32_t dst, const void* src) {
    asm volatile("cp.async.cg.shared.global [%0], [%1], 16;" ::"r"(dst), "l"(src) : "memory");
}
__device__ __forceinline__ float bf_lo(uint32_t u) { return __uint_as_float(u << 16); }
__device__ __forceinline__ float bf_hi(uint32_t u) { return __uint_as_float(u & 0xffff0000u); }
__device__ __forceinline__ float bf_round(float x) { return __bfloat162float(__float2bfloat16_rn(x)); }
__device__ __forceinline__ uint32_t ld_pair(const __nv_bfloat16* p) {
    return __ldg(reinterpret_cast<const uint32_t*>(p));
}
__device__ __forceinline__ unsigned int ld_relaxed(const unsigned int* p) {
    unsigned int v;
    asm volatile("ld.relaxed.gpu.global.u32 %0, [%1];" : "=r"(v) : "l"(p) : "memory");
    return v;
}
__device__ __forceinline__ unsigned long long pack_rec(float a, float b, uint32_t tag) {
    const uint32_t x = (__float_as_uint(a) & ~15u) | (tag & 15u), y = (__float_as_uint(b) & ~15u) | (tag >> 4);
    return ((unsigned long long)y << 32) | x;
}
__device__ __forceinline__ void st_rec(unsigned long long* p, float a, float b, uint32_t tag) {
    asm volatile("st.relaxed.gpu.global.b64 [%0], %1;" ::"l"(p), "l"(pack_rec(a, b, tag)) : "memory");
}
__device__ __forceinline__ float rec_lo(unsigned long long w) { return __uint_as_float((uint32_t)w & ~15u); }
__device__ __forceinline__ float rec_hi(unsigned long long w) { return __uint_as_float((uint32_t)(w >> 32) & ~15u); }
__device__ __forceinline__ unsigned long long ld_rec1(const unsigned long long* p) {
    unsigned long long x;
    asm volatile("ld.relaxed.gpu.global.b64 %0, [%1];" : "=l"(x) : "l"(p) : "memory");
    return x;
}
__device__ __forceinline__ uint32_t rec_bad(unsigned long long w, uint32_t tlo, uint32_t thi) {
    return (((uint32_t)w ^ tlo) | ((uint32_t)(w >> 32) ^ thi)) & 15u;
}
__device__ __forceinline__ void st_ml(unsigned long long* p, float m, float l, uint32_t tag) {
    const uint32_t y = ((__float_as_uint(l) + 0x80u) & ~0xffu) | tag;
    asm volatile("st.relaxed.gpu.global.b64 [%0], %1;" ::"l"(p), "l"(((unsigned long long)y << 32) | __float_as_uint(m)) : "memory");
}
__device__ __forceinline__ uint32_t ml_bad(unsigned long long w, uint32_t tag) { return ((uint32_t)(w >> 32) ^ tag) & 0xffu; }
__device__ __forceinline__ float ml_m(unsigned long long w) { return __uint_as_float((uint32_t)w); }
__device__ __forceinline__ float ml_l(unsigned long long w) { return __uint_as_float((uint32_t)(w >> 32) & ~0xffu); }
__device__ __forceinline__ float warp_max(float v) {
    const int b = __float_as_int(v);
    const int k = __reduce_max_sync(0xffffffffu, b ^ ((b >> 31) & 0x7fffffff));
    return __int_as_float(k ^ ((k >> 31) & 0x7fffffff));
}
__device__ __forceinline__ uint32_t round_tag(unsigned int epoch, int r) {
    constexpr unsigned kUses = (kRounds + kPR - 1) / kPR;
    return (epoch * kUses + (unsigned)(r / kPR)) % 255u + 1u;
}

__device__ __forceinline__ void rotate_q(uint32_t* qrow, int p, uint32_t c_lo, uint32_t c_hi, uint32_t s_lo, uint32_t s_hi) {
    const uint32_t lo = qrow[p], hi = qrow[p + 48];
    const float a0 = bf_round(bf_lo(lo) * bf_lo(c_lo)) + bf_round(-bf_lo(hi) * bf_lo(s_lo));
    const float a1 = bf_round(bf_hi(lo) * bf_hi(c_lo)) + bf_round(-bf_hi(hi) * bf_hi(s_lo));
    const float b0 = bf_round(bf_lo(hi) * bf_lo(c_hi)) + bf_round(bf_lo(lo) * bf_lo(s_hi));
    const float b1 = bf_round(bf_hi(hi) * bf_hi(c_hi)) + bf_round(bf_hi(lo) * bf_hi(s_hi));
    const __nv_bfloat162 ua = __floats2bfloat162_rn(a0, a1), ub = __floats2bfloat162_rn(b0, b1);
    qrow[p] = *reinterpret_cast<const uint32_t*>(&ua);
    qrow[p + 48] = *reinterpret_cast<const uint32_t*>(&ub);
}
__device__ __forceinline__ int deferred_to(int m, int r) {
    return (unsigned)(r - kDef0) < (unsigned)kFHeads ? (m / kFG - kF * (r - kDef0)) & (kFHeads - 1) : kF;
}

__global__ void __launch_bounds__(kThreads, 1)
attn_kernel(const __nv_bfloat16* __restrict__ q, const int* __restrict__ qk,
            const __nv_bfloat16* __restrict__ ksc, const __nv_bfloat16* __restrict__ kzp,
            const int* __restrict__ qv, const __nv_bfloat16* __restrict__ vsc,
            const __nv_bfloat16* __restrict__ vzp, const __nv_bfloat16* __restrict__ qcos,
            const __nv_bfloat16* __restrict__ qsin, const __nv_bfloat16* __restrict__ kcos,
            const __nv_bfloat16* __restrict__ ksin, __nv_bfloat16* __restrict__ out,
            const __grid_constant__ CUtensorMap tmv) {
    extern __shared__ __align__(128) unsigned char smem[];
    const int warp = threadIdx.x >> 5, lane = threadIdx.x & 31;
    const uint32_t full0 = s2u(smem + kOffBar), empty0 = full0 + kNS * 8;
    const uint32_t sfull = empty0 + kNS * 8, sempty = sfull + 16, mxbar = sempty + 16, fine = mxbar + 16;
    volatile unsigned int* s_misc = reinterpret_cast<volatile unsigned int*>(smem + kOffMisc);
    uint64_t pol = 0;

    if (threadIdx.x == kCW * 32 && blockIdx.x < kStream) {
        const int m = blockIdx.x % kSlots;
        const uint32_t sm0 = s2u(smem);
        const int pa = blockIdx.x & 3;
        asm volatile("cp.async.bulk.prefetch.L2.global [%0], %1;"
                     ::"l"((pa == 0 ? ksc : pa == 1 ? kzp : pa == 2 ? vsc : vzp) + (blockIdx.x >> 2) * (kNH * kS * 4 / kStream)),
                       "n"(kNH * kS * 4 / kStream * 2) : "memory");
        for (int i = 0; i < kNS; i++) mbar_init(full0 + 8 * i, 1);
        asm volatile("fence.mbarrier_init.release.cluster;" ::: "memory");
        asm volatile("createpolicy.fractional.L2::evict_first.b64 %0, 1.0;" : "=l"(pol));
        mbar_expect(full0 + 8, kChunk);
        bulk_g2s_stream(sm0 + kChunk, qk + (size_t)blockIdx.x * (kRows * kD), kChunk, full0 + 8, pol);
        mbar_expect(full0, kChunk);
        bulk_g2s(sm0, kcos + (size_t)m * kRows * kD, kChunk / 2, full0);
        bulk_g2s(sm0 + kChunk / 2, ksin + (size_t)m * kRows * kD, kChunk / 2, full0);
        mbar_expect(full0 + 16, kChunk);
        bulk_g2s_stream(sm0 + 2 * kChunk, qk + (size_t)(blockIdx.x + kStream) * (kRows * kD), kChunk, full0 + 16, pol);
    }

    if (blockIdx.x >= kStream) {
        const int team = blockIdx.x - kStream;
        if (threadIdx.x == 0) s_misc[0] = ld_relaxed(&g_epoch);
        __syncthreads();
        if (threadIdx.x == 0 && atomicAdd(&g_arrive, 1u) == kGrid - 1) { g_arrive = 0u; g_epoch = s_misc[0] + 1u; }
        if (warp >= 3 * kMG) return;
        const int grp = warp / 3, t = threadIdx.x - grp * 96;
        constexpr int kRecBytes = kSlots * kRecWords * 8;
        uint32_t mph = 0;
        if (t == 0) {
            mbar_init(s2u(smem + kOffBar) + grp * 8, 1);
            asm volatile("fence.mbarrier_init.release.cluster;" ::: "memory");
        }
        asm volatile("bar.sync %0, 96;" ::"r"(3 + grp) : "memory");
        for (int r = grp; r < kRounds; r += kMG) {
            const int g = r % kMG;
            const int tt = threadIdx.x - g * 96, qd = tt % 48, half = tt / 48;
            const uint32_t tag = round_tag(s_misc[0], r);
            const uint32_t tlo = tag & 15u, thi = tag >> 4;
            const unsigned long long* rec = g_rec + ((size_t)(r % kPR) * kStream + team * kSlots) * kRecWords;
            unsigned long long ml, x[16], y[16];
            {
                const unsigned long long* buf = reinterpret_cast<const unsigned long long*>(smem + g * kRecBytes);
                const uint32_t mb = s2u(smem + kOffBar) + g * 8;
                for (int it = 0;; it++) {
                    if (tt < 32) {
                        for (int i2 = 0;; i2++) {
                            ml = ld_rec1(rec + lane * kRecWords + 96);
                            if (__all_sync(0xffffffffu, ml_bad(ml, tag) == 0)) break;
                            if (i2 > kSpin) __trap();
                            __nanosleep(kSleep);
                        }
                        if (tt == 0) {
                            mbar_expect(mb, kRecBytes);
                            bulk_g2s(s2u(buf), rec, kRecBytes, mb);
                        }
                    }
                    mbar_wait(mb, mph);
                    mph ^= 1;
                    ml = buf[lane * kRecWords + 96];
                    const unsigned long long* po = buf + half * 16 * kRecWords + 2 * qd;
                    uint32_t bad = ml_bad(ml, tag);
#pragma unroll
                    for (int i = 0; i < 16; i++) {
                        const ulonglong2 u = *reinterpret_cast<const ulonglong2*>(po + i * kRecWords);
                        x[i] = u.x; y[i] = u.y;
                        bad |= rec_bad(x[i], tlo, thi) | rec_bad(y[i], tlo, thi);
                    }
                    uint32_t anybad;
                    asm volatile("{\n.reg .pred p, q;\nsetp.ne.u32 q, %1, 0;\nbarrier.cta.red.or.aligned.pred p, %2, 96, q;\nselp.u32 %0, 1, 0, p;\n}"
                                 : "=r"(anybad) : "r"(bad), "r"(3 + g) : "memory");
                    if (!anybad) break;
                    if (it > kSpin) __trap();
                }
            }
            const float M = ml_m(ml);
            const float MM = warp_max(M);
            const float w = exp2f(M - MM);
            float LL = w * ml_l(ml);
#pragma unroll
            for (int o = 16; o > 0; o >>= 1) LL += __shfl_xor_sync(0xffffffffu, LL, o);
            float4 a = make_float4(0.f, 0.f, 0.f, 0.f);
#pragma unroll
            for (int i = 0; i < 16; i++) {
                const float wi = __shfl_sync(0xffffffffu, w, half * 16 + i);
                a.x = fmaf(wi, rec_lo(x[i]), a.x);
                a.y = fmaf(wi, rec_hi(x[i]), a.y);
                a.z = fmaf(wi, rec_lo(y[i]), a.z);
                a.w = fmaf(wi, rec_hi(y[i]), a.w);
            }
            float* rb = reinterpret_cast<float*>(smem + kMG * kRecBytes) + (2 * g + ((r / kMG) & 1)) * kD + 4 * qd;
            if (half == 1) *reinterpret_cast<float4*>(rb) = a;
            asm volatile("bar.sync %0, 96;" ::"r"(3 + g) : "memory");
            if (half == 0) {
                const float4 u = *reinterpret_cast<float4*>(rb);
                if ((unsigned)(r - kDef0) < (unsigned)kFHeads) {
                    unsigned long long* pre = g_pre + (size_t)(team * kFHeads + r - kDef0) * kRecWords;
                    const uint32_t ptag = s_misc[0] % 255u + 1u;
                    st_rec(pre + 2 * qd, a.x + u.x, a.y + u.y, ptag);
                    st_rec(pre + 2 * qd + 1, a.z + u.z, a.w + u.w, ptag);
                    if (qd == 0) st_ml(pre + 96, MM, LL, ptag);
                } else {
                    const float inv = __fdividef(1.0f, LL);
                    const __nv_bfloat162 o0 = __floats2bfloat162_rn((a.x + u.x) * inv, (a.y + u.y) * inv);
                    const __nv_bfloat162 o1 = __floats2bfloat162_rn((a.z + u.z) * inv, (a.w + u.w) * inv);
                    uint2 ov;
                    ov.x = *reinterpret_cast<const uint32_t*>(&o0);
                    ov.y = *reinterpret_cast<const uint32_t*>(&o1);
                    *reinterpret_cast<uint2*>(out + (size_t)(kTeams * r + team) * kD + 4 * qd) = ov;
                }
            }
            if (tt == 95)
                asm volatile("st.relaxed.gpu.global.u32 [%0], %1;" ::"l"(&g_mdone[(team * kMG + g) * 32]), "r"(s_misc[0] * kRounds + r + 1) : "memory");
        }
        return;
    }

    const int m = blockIdx.x % kSlots, team = blockIdx.x / kSlots;
    const int row0 = m * kRows;

    if (warp == kCW) {
        unsigned int epoch = 0;
        const size_t off0 = ((size_t)team * kS + row0) * kD;
        const uint32_t sm0 = s2u(smem);
        if (lane == 0) {
            epoch = ld_relaxed(&g_epoch);
            s_misc[0] = epoch;
        }
        __syncwarp();
        asm volatile("bar.sync 2, %0;" ::"n"(kThreads) : "memory");
        if (lane == 0) {
            unsigned int cum = epoch * (kStream * (2 * kRounds - 1)) + 2 * kStream;
            int slot = 3 % kNS;
            uint32_t ph = (3 / kNS) & 1;
            for (int p = 2; p < 2 * kRounds + kF; p++) {
                const bool isv = (p & 1) == 0 || p == 2 * kRounds - 1;
                const int r = p == 2 * kRounds - 1 ? kRounds - 1 : isv ? (p >> 1) - 1 : (p + 1) >> 1;
                const unsigned int need = cum - (p == 3 ? kLead3 : kLead);
                cum += (isv && (unsigned)(r - kDef0) < (unsigned)kFHeads) ? kStream - kTeams * kFG * kF : kStream;
                const bool skip = isv && deferred_to(m, r) < kF;
                const int* src = (isv ? qv : qk) + off0 + (size_t)r * kTeams * kS * kD;
                if (p == 2 * kRounds - 2) asm volatile("prefetch.tensormap [%0];" ::"l"(&tmv) : "memory");
                if (!skip) {
                    if (p > 2)
                        for (int it = 0; (int)(ld_relaxed(&g_prog) - need) < 0; it++)
                            if (it > kSpin) __trap();
                    mbar_wait(empty0 + 8 * slot, ph ^ 1);
                }
                if (p >= 2 * kRounds || skip) {
                    const int hi = m / kFG;
                    const int row = (kTeams * (kDef0 + hi) + team) * kS + ((kF * hi + p - 2 * kRounds) & (kFHeads - 1)) * kFRows;
                    const uint32_t fb = fine + 8 * kFBoxes * (p - 2 * kRounds);
#pragma unroll 1
                    for (int w = 0; w < kFBoxes; w++)
                        asm volatile("{\n.reg .pred p;\nsetp.ne.u32 p, %6, 0;\n"
                                     "@p cp.async.bulk.tensor.2d.shared::cluster.global.tile.mbarrier::complete_tx::bytes.L2::cache_hint [%0], [%1, {%2, %3}], [%4], %5;\n}"
                                     ::"r"(sm0 + slot * kChunk + w * (kChunk / kFBoxes)), "l"(&tmv), "r"((m % kFG) * kFW), "r"(row + w * (kFRows / kFBoxes)),
                                       "r"(fb + 8 * w), "l"(pol), "r"((uint32_t)!skip) : "memory");
                    if (skip) continue;
                } else {
                    mbar_expect(full0 + 8 * slot, kChunk);
                    bulk_g2s_stream(sm0 + slot * kChunk, src, kChunk, full0 + 8 * slot, pol);
                }
                if (++slot == kNS) { slot = 0; ph ^= 1; }
            }
        }
    } else if (warp == kCW + 1) {
        {
            const int i = kNS + lane;
            if (i < 2 * kNS + 6) mbar_init(full0 + 8 * i, (i >= 2 * kNS + 2 && i < 2 * kNS + 4) ? 1 : kCW);
            asm volatile("fence.mbarrier_init.release.cluster;" ::: "memory");
        }
        asm volatile("bar.sync 2, %0;" ::"n"(kThreads) : "memory");
        const unsigned int epoch = s_misc[0];
        if (lane == 0 && atomicAdd(&g_arrive, 1u) == kGrid - 1) { g_arrive = 0u; g_epoch = epoch + 1u; }
        {
            const uint32_t sm0 = s2u(smem);
            const int a = lane >> 3;
            const __nv_bfloat16* src = (a == 0 ? ksc : a == 1 ? kzp : a == 2 ? vsc : vzp) + (size_t)team * kS + row0 + (lane & 7) * 8;
            const __nv_bfloat16* qs = q + team * kD + lane * 8;
#pragma unroll 1
            for (int r = kEarly; r < kRounds; r++) {
                cp16(sm0 + kOffScal + r * 512 + lane * 16, src + (size_t)r * (kTeams * kS));
                if (lane < 24) cp16(sm0 + kOffQ + r * (kD * 2) + lane * 16, qs + r * (kTeams * kD));
                if (r == 2 * kEarly - 1 || r == kRounds - 1) asm volatile("cp.async.commit_group;" ::: "memory");
            }
        }
        uint32_t cs[2][4];
#pragma unroll
        for (int i = 0; i < 2; i++) {
            const int p = (lane + 32 * i) % 48;
            cs[i][0] = ld_pair(qcos + 2 * p); cs[i][1] = ld_pair(qcos + 2 * p + 96);
            cs[i][2] = ld_pair(qsin + 2 * p); cs[i][3] = ld_pair(qsin + 2 * p + 96);
        }
        asm volatile("cp.async.wait_group 1;" ::: "memory");
        __syncwarp();
        for (int r = 0; r < kRounds; r++) {
            const float* sc = reinterpret_cast<const float*>(smem + kOffSc) + (r & 1) * (kCW * kScStride);
            const uint32_t tag = round_tag(epoch, r);
            unsigned long long* rec = g_rec + ((size_t)(r % kPR) * kStream + team * kSlots + m) * kRecWords;
            if (r == kPrep - 1) {
                for (int i = lane; i < kF * kFBoxes; i += 32) mbar_init(fine + 8 * i, 1);
                asm volatile("fence.mbarrier_init.release.cluster;" ::: "memory");
                for (int i = lane; i < kF * kFBoxes; i += 32) mbar_expect(fine + 8 * i, kChunk / kFBoxes);
                asm volatile("fence.proxy.async.shared::cta;" ::: "memory");
            }
            if (r == kPrep) {
                const unsigned long long* pre = g_pre + (size_t)(team * kFHeads + m / kFG) * kRecWords;
                const unsigned long long* lgp = g_lg + (size_t)(team * kFHeads + m / kFG) * (kF * kFRows);
                const uint32_t ptag = epoch % 255u + 1u;
                unsigned long long ml, po;
                for (int it = 0;; it++) {
                    ml = ld_rec1(pre + 96);
                    po = ld_rec1(pre + (m % kFG) * (kFW / 2) + lane % (kFW / 2));
                    if (!(ml_bad(ml, ptag) | rec_bad(po, ptag & 15u, ptag >> 4))) break;
                    if (it > kSpin) __trap();
                }
                const float inv = 1.0f / ml_l(ml);
                if (lane < kFW / 2) {
                    reinterpret_cast<float*>(smem + kOffFin)[lane] = rec_lo(po) * inv;
                    reinterpret_cast<float*>(smem + kOffFin)[kFW / 2 + lane] = rec_hi(po) * inv;
                }
#pragma unroll 1
                for (int c = 0; c < kF; c++) {
                    unsigned long long u[8];
                    for (int it = 0;; it++) {
                        uint32_t bad = 0;
#pragma unroll
                        for (int k = 0; k < 8; k++) {
                            u[k] = ld_rec1(lgp + c * kFRows + 32 * k + lane);
                            bad |= ml_bad(u[k], ptag);
                        }
                        if (!bad) break;
                        if (it > kSpin) __trap();
                    }
#pragma unroll
                    for (int k = 0; k < 8; k++)
                        reinterpret_cast<float*>(smem + kOffW)[c * kFRows + 32 * k + lane] = ml_l(u[k]) * exp2f(ml_m(u[k]) - ml_m(ml)) * inv;
                }
                __syncwarp();
            }
            if (r == kEarly) {
                asm volatile("cp.async.wait_all;" ::: "memory");
                __syncwarp();
            }
            if (r + kEarly < kRounds) {
                uint32_t* qrow = reinterpret_cast<uint32_t*>(smem + kOffQ + (r + kEarly) * (kD * 2));
                rotate_q(qrow, lane, cs[0][0], cs[0][1], cs[0][2], cs[0][3]);
                if (lane < 16) rotate_q(qrow, lane + 32, cs[1][0], cs[1][1], cs[1][2], cs[1][3]);
            }
            if (r >= kPR) {
                const unsigned int* mdone = &g_mdone[(team * kMG + r % kMG) * 32];
                const unsigned int need = epoch * kRounds + r - kPR + 1;
                for (int it = 0; (int)(ld_relaxed(mdone) - need) < 0; it++)
                    if (it > kSpin) __trap();
            }
            mbar_wait(sfull + 8 * (r & 1), (r >> 1) & 1);
            const float M = sc[0];
            float L = lane < kCW ? sc[lane * kScStride + 1] : 0.f;
            float acc[2][6];
#pragma unroll
            for (int ww = 0; ww < kCW; ww++) {
#pragma unroll
                for (int j = 0; j < 3; j++) {
                    const float2 t = *reinterpret_cast<const float2*>(sc + ww * kScStride + 4 + 64 * j + 2 * lane);
                    acc[ww & 1][2 * j] = ww < 2 ? t.x : acc[ww & 1][2 * j] + t.x;
                    acc[ww & 1][2 * j + 1] = ww < 2 ? t.y : acc[ww & 1][2 * j + 1] + t.y;
                }
                if ((ww & 3) == 3 && ww < 15) L += __shfl_xor_sync(0xffffffffu, L, 8 >> (ww >> 2));
            }
            L += __shfl_xor_sync(0xffffffffu, L, 1);
#pragma unroll
            for (int j = 0; j < 3; j++)
                st_rec(rec + 32 * j + lane, acc[0][2 * j] + acc[1][2 * j], acc[0][2 * j + 1] + acc[1][2 * j + 1], tag);
            if (lane == 0) st_ml(rec + 96, M, L, tag);
            __syncwarp();
            if (lane == 0) mbar_arrive(sempty + 8 * (r & 1));
        }
    } else {
        int dp[3];
#pragma unroll
        for (int j = 0; j < 3; j++) dp[j] = (64 * j + 2 * lane + 96) % kD;
        {
            const uint32_t sm0 = s2u(smem);
            if (warp < kEarly) {
                const int a = lane >> 3;
                const __nv_bfloat16* src = (a == 0 ? ksc : a == 1 ? kzp : a == 2 ? vsc : vzp);
                cp16(sm0 + kOffScal + threadIdx.x * 16, src + (size_t)(kTeams * warp + team) * kS + row0 + (lane & 7) * 8);
            } else if (warp < 2 * kEarly && lane < 24) {
                cp16(sm0 + kOffQ + (warp - kEarly) * (kD * 2) + lane * 16, q + (size_t)(kTeams * (warp - kEarly) + team) * kD + lane * 8);
            }
            asm volatile("cp.async.commit_group;" ::: "memory");
        }
        const int p = threadIdx.x % 48, g = threadIdx.x / 48;
        const uint32_t c_lo = ld_pair(qcos + 2 * p), c_hi = ld_pair(qcos + 2 * p + 96);
        const uint32_t s_lo = ld_pair(qsin + 2 * p), s_hi = ld_pair(qsin + 2 * p + 96);
        float kc[kR][6], ks[kR][6];
        asm volatile("bar.sync 2, %0;" ::"n"(kThreads) : "memory");
        mbar_wait(full0, 0);
#pragma unroll
        for (int i = 0; i < kR; i++) {
            const unsigned char* cb = smem + (warp * kR + i) * (kD * 2);
#pragma unroll
            for (int j = 0; j < 3; j++) {
                const uint32_t uc = *reinterpret_cast<const uint32_t*>(cb + 128 * j + 4 * lane);
                const uint32_t us = *reinterpret_cast<const uint32_t*>(cb + kChunk / 2 + 2 * dp[j]);
                kc[i][2 * j] = bf_lo(uc); kc[i][2 * j + 1] = bf_hi(uc);
                const float sg = (j == 0 || (j == 1 && lane < 16)) ? 1.f : -1.f;
                ks[i][2 * j] = sg * bf_lo(us); ks[i][2 * j + 1] = sg * bf_hi(us);
            }
        }
        __syncwarp();
        if (lane == 0) mbar_arrive(empty0);
        asm volatile("cp.async.wait_group 0;" ::: "memory");
        asm volatile("bar.sync 1, %0;" ::"n"(kCW * 32) : "memory");
        if (g < kEarly) rotate_q(reinterpret_cast<uint32_t*>(smem + kOffQ + g * (kD * 2)), p, c_lo, c_hi, s_lo, s_hi);
        asm volatile("bar.sync 1, %0;" ::"n"(kCW * 32) : "memory");
        const float scale_log2e = 1.4426950408889634f * rsqrtf((float)kD);
        float* my0 = reinterpret_cast<float*>(smem + kOffSc) + warp * kScStride;

        float* s_max = reinterpret_cast<float*>(smem + kOffMax);
        int slot = 1;
        uint32_t ph = 0;
        float lgc[kR] = {0.f, 0.f, 0.f, 0.f};
        for (int it = 0; it <= kRounds; it++) {
            float lg[kR];
            if (it < kRounds) {
                float qa[6], qb[6];
#pragma unroll
                for (int j = 0; j < 3; j++) {
                    const uint32_t qo = *reinterpret_cast<const uint32_t*>(smem + kOffQ + it * (kD * 2) + 2 * (64 * j + 2 * lane));
                    const uint32_t qp = *reinterpret_cast<const uint32_t*>(smem + kOffQ + it * (kD * 2) + 2 * dp[j]);
                    qa[2 * j] = bf_lo(qo); qa[2 * j + 1] = bf_hi(qo);
                    qb[2 * j] = bf_lo(qp); qb[2 * j + 1] = bf_hi(qp);
                }
                const unsigned char* sp = smem + kOffScal + it * (4 * kRows * 2) + warp * (kR * 2);
                const uint2 uks = *reinterpret_cast<const uint2*>(sp);
                const uint2 ukz = *reinterpret_cast<const uint2*>(sp + kRows * 2);
                const float kz[4] = {bf_lo(ukz.x), bf_hi(ukz.x), bf_lo(ukz.y), bf_hi(ukz.y)};
                const float sk[4] = {bf_lo(uks.x), bf_hi(uks.x), bf_lo(uks.y), bf_hi(uks.y)};
                mbar_wait(full0 + 8 * slot, ph);
                if (threadIdx.x == 0) asm volatile("red.relaxed.gpu.global.add.u32 [%0], 1;" ::"l"(&g_prog) : "memory");
                const unsigned char* kb = smem + slot * kChunk + warp * (kR * kRowBytes) + lane * 8;
#pragma unroll
                for (int i = 0; i < kR; i++) {
                    float dot = 0.f;
#pragma unroll
                    for (int j = 0; j < 3; j++) {
                        const int2 kk = *reinterpret_cast<const int2*>(kb + i * kRowBytes + 256 * j);
                        const float e0 = qa[2 * j] * kc[i][2 * j] + qb[2 * j] * ks[i][2 * j];
                        const float e1 = qa[2 * j + 1] * kc[i][2 * j + 1] + qb[2 * j + 1] * ks[i][2 * j + 1];
                        dot = fmaf((float)kk.x - kz[i], e0, dot);
                        dot = fmaf((float)kk.y - kz[i], e1, dot);
                    }
                    lg[i] = dot;
                }
                __syncwarp();
                if (lane == 0) mbar_arrive(empty0 + 8 * slot);
                if (++slot == kNS) { slot = 0; ph ^= 1; }
#pragma unroll
                for (int o = 16; o > 0; o >>= 1) {
#pragma unroll
                    for (int i = 0; i < kR; i++) lg[i] += __shfl_xor_sync(0xffffffffu, lg[i], o);
                }
                float mw = -INFINITY;
#pragma unroll
                for (int i = 0; i < kR; i++) {
                    lg[i] = lg[i] * sk[i] * scale_log2e;
                    mw = fmaxf(mw, lg[i]);
                }
                if (lane == 0) {
                    s_max[(it & 3) * kCW + warp] = mw;
                    mbar_arrive(mxbar + 8 * (it & 1));
                }
            }
            if (it > 0) {
                const int r = it - 1;
                float* my = my0 + (r & 1) * (kCW * kScStride);
                const int df = deferred_to(m, r);
                const unsigned char* sp = smem + kOffScal + r * (4 * kRows * 2) + warp * (kR * 2);
                const uint2 uvs = *reinterpret_cast<const uint2*>(sp + 2 * kRows * 2);
                const uint2 uvz = *reinterpret_cast<const uint2*>(sp + 3 * kRows * 2);
                const float vz[4] = {bf_lo(uvz.x), bf_hi(uvz.x), bf_lo(uvz.y), bf_hi(uvz.y)};
                const float sv[4] = {bf_lo(uvs.x), bf_hi(uvs.x), bf_lo(uvs.y), bf_hi(uvs.y)};
                mbar_wait(mxbar + 8 * (r & 1), (r >> 1) & 1);
                float M;
                {
                    const float4* pm4 = reinterpret_cast<const float4*>(s_max + (r & 3) * kCW);
                    const float4 m0 = pm4[0], m1 = pm4[1], m2 = pm4[2], m3 = pm4[3];
                    M = fmaxf(fmaxf(fmaxf(fmaxf(m0.x, m0.y), fmaxf(m0.z, m0.w)), fmaxf(fmaxf(m1.x, m1.y), fmaxf(m1.z, m1.w))),
                              fmaxf(fmaxf(fmaxf(m2.x, m2.y), fmaxf(m2.z, m2.w)), fmaxf(fmaxf(m3.x, m3.y), fmaxf(m3.z, m3.w))));
                }
                float lw = 0.f, cz = 0.f, pv[kR];
#pragma unroll
                for (int i = 0; i < kR; i++) {
                    const float p = exp2f(lgc[i] - M);
                    lw += p;
                    pv[i] = p * sv[i];
                    cz = fmaf(pv[i], vz[i], cz);
                }
                mbar_wait(sempty + 8 * (r & 1), ((r >> 1) & 1) ^ 1);
                if (lane == 0) { my[0] = M; my[1] = lw; }
                float acc[6] = {-cz, -cz, -cz, -cz, -cz, -cz};
                if (df < kF) {
                    if (lane < kR)
                        st_ml(g_lg + ((team * kFHeads + r - kDef0) * kF + df) * kFRows + (m % kFG) * kRows + warp * kR + lane, M,
                              lane == 0 ? pv[0] : lane == 1 ? pv[1] : lane == 2 ? pv[2] : pv[3], s_misc[0] % 255u + 1u);
                } else {
                    mbar_wait(full0 + 8 * slot, ph);
                    if (threadIdx.x == 0) asm volatile("red.relaxed.gpu.global.add.u32 [%0], 1;" ::"l"(&g_prog) : "memory");
                    const unsigned char* vb = smem + slot * kChunk + warp * (kR * kRowBytes) + lane * 8;
#pragma unroll
                    for (int i = 0; i < kR; i++) {
#pragma unroll
                        for (int j = 0; j < 3; j++) {
                            const int2 vv = *reinterpret_cast<const int2*>(vb + i * kRowBytes + 256 * j);
                            acc[2 * j] = fmaf(pv[i], (float)vv.x, acc[2 * j]);
                            acc[2 * j + 1] = fmaf(pv[i], (float)vv.y, acc[2 * j + 1]);
                        }
                    }
                    __syncwarp();
                    if (lane == 0) mbar_arrive(empty0 + 8 * slot);
                    if (++slot == kNS) { slot = 0; ph ^= 1; }
                }
#pragma unroll
                for (int j = 0; j < 3; j++)
                    *reinterpret_cast<float2*>(my + 4 + 64 * j + 2 * lane) = make_float2(acc[2 * j], acc[2 * j + 1]);
                __syncwarp();
                if (lane == 0) mbar_arrive(sfull + 8 * (r & 1));
            }
#pragma unroll
            for (int i = 0; i < kR; i++) lgc[i] = lg[i];
        }
        {
            const int cp = lane < kFW / 2 ? lane : 0;
            const int ft = threadIdx.x < kFW ? threadIdx.x : 0;
            const float fin = reinterpret_cast<const float*>(smem + kOffFin)[ft];
            __nv_bfloat16* op = out + (size_t)(kTeams * (kDef0 + m / kFG) + team) * kD + (m % kFG) * kFW + 2 * (ft % (kFW / 2)) + ft / (kFW / 2);
            float a0 = 0.f, a1 = 0.f, b0 = 0.f, b1 = 0.f;
#pragma unroll 1
            for (int f = 0; f < kF; f++) {
                const float* sw = reinterpret_cast<const float*>(smem + kOffW) + f * kFRows + (warp >> 2) * 16 + (warp & 3) * 4;
                const unsigned char* vb = smem + slot * kChunk + ((warp >> 2) * 16 + (warp & 3) * 4) * (kFW * 4) + cp * 8;
                const uint32_t fb = fine + (f * kFBoxes + (warp >> 2)) * 8;
                float* part = reinterpret_cast<float*>(smem + kOffPart) + f * (kFW * kPartStride);
                float4 w[4];
#pragma unroll
                for (int k = 0; k < 4; k++) w[k] = *reinterpret_cast<const float4*>(sw + 64 * k);
#pragma unroll
                for (int k = 0; k < 4; k++) {
                    mbar_wait(fb + 32 * k, 0);
                    const int2 v0 = *reinterpret_cast<const int2*>(vb + k * (64 * kFW * 4));
                    const int2 v1 = *reinterpret_cast<const int2*>(vb + k * (64 * kFW * 4) + kFW * 4);
                    const int2 v2 = *reinterpret_cast<const int2*>(vb + k * (64 * kFW * 4) + 2 * kFW * 4);
                    const int2 v3 = *reinterpret_cast<const int2*>(vb + k * (64 * kFW * 4) + 3 * kFW * 4);
                    a0 = fmaf(w[k].x, (float)v0.x, a0); a1 = fmaf(w[k].x, (float)v0.y, a1);
                    b0 = fmaf(w[k].y, (float)v1.x, b0); b1 = fmaf(w[k].y, (float)v1.y, b1);
                    a0 = fmaf(w[k].z, (float)v2.x, a0); a1 = fmaf(w[k].z, (float)v2.y, a1);
                    b0 = fmaf(w[k].w, (float)v3.x, b0); b1 = fmaf(w[k].w, (float)v3.y, b1);
                }
                if (lane < kFW / 2) {
                    part[lane * kPartStride + warp] = a0 + b0;
                    part[(kFW / 2 + lane) * kPartStride + warp] = a1 + b1;
                }
                if (warp >= 2) {
                    asm volatile("bar.arrive %0, %1;" ::"r"(3 + f), "n"(kCW * 32) : "memory");
                    if (threadIdx.x == kCW * 32 - 32 && f < kF - 1) asm volatile("red.relaxed.gpu.global.add.u32 [%0], 1;" ::"l"(&g_prog) : "memory");
                } else {
                    asm volatile("bar.sync %0, %1;" ::"r"(3 + f), "n"(kCW * 32) : "memory");
                    const float4* ps = reinterpret_cast<const float4*>(part + ft * kPartStride);
                    const float4 p0 = ps[0], p1 = ps[1], p2 = ps[2], p3 = ps[3];
                    const float sum = (((p0.x + p0.y) + (p0.z + p0.w)) + ((p1.x + p1.y) + (p1.z + p1.w))) +
                                      (((p2.x + p2.y) + (p2.z + p2.w)) + ((p3.x + p3.y) + ((p3.z + p3.w) + fin)));
                    asm volatile("{\n.reg .pred p;\n.reg .b16 h;\nsetp.ne.u32 p, %2, 0;\ncvt.rn.bf16.f32 h, %1;\n@p st.global.b16 [%0], h;\n}"
                                 ::"l"(op), "f"(sum), "r"((uint32_t)(f == kF - 1 && threadIdx.x < kFW)) : "memory");
                }
                if (++slot == kNS) slot = 0;
            }
        }
    }
}

__global__ void __launch_bounds__(256)
attn_fallback(const __nv_bfloat16* __restrict__ q, const int* __restrict__ qk,
              const __nv_bfloat16* __restrict__ ksc, const __nv_bfloat16* __restrict__ kzp,
              const int* __restrict__ qv, const __nv_bfloat16* __restrict__ vsc,
              const __nv_bfloat16* __restrict__ vzp, const __nv_bfloat16* __restrict__ qcos,
              const __nv_bfloat16* __restrict__ qsin, const __nv_bfloat16* __restrict__ kcos,
              const __nv_bfloat16* __restrict__ ksin, __nv_bfloat16* __restrict__ out) {
    __shared__ float qr[kD], lg[kS], red[8];
    const int h = blockIdx.x, t = threadIdx.x, warp = t >> 5, lane = t & 31;
    if (t < kD) {
        const float x = __bfloat162float(q[h * kD + t]);
        const float y = t < kD / 2 ? -__bfloat162float(q[h * kD + t + kD / 2]) : __bfloat162float(q[h * kD + t - kD / 2]);
        qr[t] = bf_round(bf_round(x * __bfloat162float(qcos[t])) + bf_round(y * __bfloat162float(qsin[t])));
    }
    __syncthreads();
    const float scale_log2e = 1.4426950408889634f * rsqrtf((float)kD);
    float mw = -INFINITY;
    for (int s = warp; s < kS; s += 8) {
        const size_t row = (size_t)h * kS + s;
        const float z = __bfloat162float(kzp[row]);
        float dot = 0.f;
        for (int d = lane; d < kD; d += 32) {
            const int dp = d < kD / 2 ? d + kD / 2 : d - kD / 2;
            const float sn = __bfloat162float(ksin[s * kD + dp]);
            const float e = qr[d] * __bfloat162float(kcos[s * kD + d]) + qr[dp] * (d < kD / 2 ? sn : -sn);
            dot = fmaf((float)qk[row * kD + d] - z, e, dot);
        }
        for (int o = 16; o > 0; o >>= 1) dot += __shfl_xor_sync(0xffffffffu, dot, o);
        dot = dot * __bfloat162float(ksc[row]) * scale_log2e;
        if (lane == 0) lg[s] = dot;
        mw = fmaxf(mw, dot);
    }
    if (lane == 0) red[warp] = mw;
    __syncthreads();
    float M = red[0];
    for (int i = 1; i < 8; i++) M = fmaxf(M, red[i]);
    __syncthreads();
    float l = 0.f;
    for (int s = t; s < kS; s += 256) { const float p = exp2f(lg[s] - M); l += p; lg[s] = p; }
    for (int o = 16; o > 0; o >>= 1) l += __shfl_xor_sync(0xffffffffu, l, o);
    if (lane == 0) red[warp] = l;
    __syncthreads();
    float L = 0.f;
    for (int i = 0; i < 8; i++) L += red[i];
    if (t < kD) {
        float acc = 0.f;
        for (int s = 0; s < kS; s++) {
            const size_t row = (size_t)h * kS + s;
            acc = fmaf(lg[s] * __bfloat162float(vsc[row]), (float)qv[row * kD + t] - __bfloat162float(vzp[row]), acc);
        }
        out[h * kD + t] = __float2bfloat16_rn(acc / L);
    }
}

}

extern "C" void kernel_launch(void* const* d_in, const int* in_sizes, int n_in, void* d_out, int out_size) {
    const __nv_bfloat16* q = (const __nv_bfloat16*)d_in[0];
    const int* qk = (const int*)d_in[1];
    const __nv_bfloat16* ksc = (const __nv_bfloat16*)d_in[2];
    const __nv_bfloat16* kzp = (const __nv_bfloat16*)d_in[3];
    const int* qv = (const int*)d_in[4];
    const __nv_bfloat16* vsc = (const __nv_bfloat16*)d_in[5];
    const __nv_bfloat16* vzp = (const __nv_bfloat16*)d_in[6];
    const __nv_bfloat16* qcos = (const __nv_bfloat16*)d_in[7];
    const __nv_bfloat16* qsin = (const __nv_bfloat16*)d_in[8];
    const __nv_bfloat16* kcos = (const __nv_bfloat16*)d_in[9];
    const __nv_bfloat16* ksin = (const __nv_bfloat16*)d_in[10];

    typedef CUresult (*EncodeFn)(CUtensorMap*, CUtensorMapDataType, cuuint32_t, void*, const cuuint64_t*, const cuuint64_t*,
                                 const cuuint32_t*, const cuuint32_t*, CUtensorMapInterleave, CUtensorMapSwizzle,
                                 CUtensorMapL2promotion, CUtensorMapFloatOOBfill);
    static EncodeFn encode = nullptr;
    static int mode = 0;
    if (!mode) {
        int dev = 0, sms = 0, occ = 0;
        cudaGetDevice(&dev);
        cudaDeviceGetAttribute(&sms, cudaDevAttrMultiProcessorCount, dev);
        cudaError_t e = cudaFuncSetAttribute(attn_kernel, cudaFuncAttributeMaxDynamicSharedMemorySize, kSmemBytes);
        if (e == cudaSuccess) e = cudaOccupancyMaxActiveBlocksPerMultiprocessor(&occ, attn_kernel, kThreads, kSmemBytes);
        void* fn = nullptr;
        cudaDriverEntryPointQueryResult qr;
        if (e == cudaSuccess) e = cudaGetDriverEntryPoint("cuTensorMapEncodeTiled", &fn, cudaEnableDefault, &qr);
        encode = (EncodeFn)fn;
        mode = (e == cudaSuccess && fn && occ * sms >= kGrid) ? 1 : 2;
        (void)cudaGetLastError();
    }
    CUtensorMap tmv;
    bool fast = mode == 1;
    if (fast) {
        const cuuint64_t dims[2] = {(cuuint64_t)kD, (cuuint64_t)kNH * kS}, strides[1] = {(cuuint64_t)kRowBytes};
        const cuuint32_t box[2] = {(cuuint32_t)kFW, (cuuint32_t)(kFRows / kFBoxes)}, es[2] = {1, 1};
        fast = encode(&tmv, CU_TENSOR_MAP_DATA_TYPE_INT32, 2, (void*)qv, dims, strides, box, es, CU_TENSOR_MAP_INTERLEAVE_NONE,
                      CU_TENSOR_MAP_SWIZZLE_NONE, CU_TENSOR_MAP_L2_PROMOTION_L2_128B, CU_TENSOR_MAP_FLOAT_OOB_FILL_NONE) == CUDA_SUCCESS;
    }
    if (fast)
        attn_kernel<<<kGrid, kThreads, kSmemBytes>>>(q, qk, ksc, kzp, qv, vsc, vzp, qcos, qsin, kcos, ksin,
                                                     (__nv_bfloat16*)d_out, tmv);
    else
        attn_fallback<<<kNH, 256>>>(q, qk, ksc, kzp, qv, vsc, vzp, qcos, qsin, kcos, ksin, (__nv_bfloat16*)d_out);
}
```

```cpp
#include <cuda_runtime.h>
#include <cuda.h>
#include <cuda_bf16.h>
#include <stdint.h>

namespace {

constexpr int kB = 8, kH = 32, kS = 2048, kD = 192;
constexpr int kNH = kB * kH;
constexpr int kTeams = 4;
constexpr int kSlots = 32;
constexpr int kRows = kS / kSlots;
constexpr int kRounds = kNH / kTeams;
constexpr int kStream = kTeams * kSlots;
constexpr int kGrid = kStream + kTeams;
constexpr int kCW = 16;
constexpr int kR = kRows / kCW;
constexpr int kThreads = (kCW + 2) * 32;
constexpr int kRowBytes = kD * 4;
constexpr int kChunk = kRows * kRowBytes;
constexpr int kNS = 3;
constexpr int kHalf = kChunk / 2;
constexpr int kHRows = kRows / 2;
constexpr int kLead = 360;
constexpr int kLeadDef = 430;
constexpr int kRampEnd = 12, kRampStep = 70;
constexpr int kQuick = 20;
constexpr int kSleep = 200;
constexpr int kPR = 12;
constexpr int kScStride = 196;
constexpr int kOffScal = kNS * kChunk;
constexpr int kOffQ = kOffScal + kRounds * 4 * kRows * 2;
constexpr int kOffSc = kOffQ + kRounds * kD * 2;
constexpr int kOffBar = kOffSc + 2 * kCW * kScStride * 4;
constexpr int kF = 3;
constexpr int kFG = 4;
constexpr int kFW = kD / kFG;
constexpr int kFRows = kRows * kFG;
constexpr int kFHeads = kSlots / kFG;
constexpr int kDef0 = 16;
constexpr int kEarly = 4;
constexpr int kFBoxes = 16;
constexpr int kPrep = 40;
constexpr int kOffW = kOffScal;
constexpr int kOffFin = kOffW + kF * kFRows * 4;
constexpr int kPartStride = 20;
constexpr int kOffPart = kOffFin + kFW * 4;
constexpr int kOffMisc = kOffBar + (4 * kNS + 6 + kF * kFBoxes) * 8;
constexpr int kOffMax = kOffMisc + 16;
constexpr int kSmemBytes = kOffMax + 4 * kCW * 4;
constexpr int kRecWords = 112;
constexpr int kMG = 6;
static_assert(kNS >= 3, "ring");
static_assert(kOffBar % 8 == 0 && kOffSc % 16 == 0 && kOffMax % 16 == 0, "alignment");
static_assert(kPR % kMG == 0, "ring");
static_assert(kLead >= kStream && kS == kFHeads * kFRows && kFHeads == 8, "schedule");
static_assert(kSmemBytes <= 232448, "smem");
static_assert(kDef0 + kFHeads < kPrep && kPrep + 16 + 3 < kRounds && kEarly + kF * kFBoxes + 3 < kRounds && kOffPart <= kOffScal + (kPrep - 2) * 4 * kRows * 2 &&
              kOffPart + kF * kFW * kPartStride * 4 <= kOffScal + (kRounds - 2) * 4 * kRows * 2 && kF <= kNS && kFBoxes == kCW, "deferred rounds");

__device__ __align__(128) unsigned long long g_rec[kPR * kStream * kRecWords];
__device__ __align__(128) unsigned long long g_pre[kTeams * kFHeads * kRecWords];
__device__ __align__(128) unsigned long long g_lg[kTeams * kFHeads * kF * kFRows];
__device__ __align__(128) unsigned int g_prog;
__device__ __align__(128) unsigned int g_epoch;
__device__ __align__(128) unsigned int g_arrive;
__device__ __align__(128) unsigned int g_mdone[kTeams * kMG * 32];

constexpr int kSpin = 1 << 24;

__device__ __forceinline__ uint32_t s2u(const void* p) { return (uint32_t)__cvta_generic_to_shared(p); }
__device__ __forceinline__ void mbar_init(uint32_t a, int c) {
    asm volatile("mbarrier.init.shared::cta.b64 [%0], %1;" ::"r"(a), "r"(c));
}
__device__ __forceinline__ void mbar_wait(uint32_t a, uint32_t ph) {
    uint32_t ok;
    for (int it = 0;; it++) {
        asm volatile(
            "{\n.reg .pred p;\nmbarrier.try_wait.parity.shared::cta.b64 p, [%1], %2;\nselp.u32 %0, 1, 0, p;\n}"
            : "=r"(ok) : "r"(a), "r"(ph) : "memory");
        if (ok) break;
        if (it > kSpin) __trap();
    }
}
__device__ __forceinline__ void mbar_arrive(uint32_t a) {
    asm volatile("mbarrier.arrive.shared::cta.b64 _, [%0];" ::"r"(a) : "memory");
}
__device__ __forceinline__ void mbar_expect(uint32_t a, uint32_t bytes) {
    asm volatile("mbarrier.arrive.expect_tx.shared::cta.b64 _, [%0], %1;" ::"r"(a), "r"(bytes) : "memory");
}
__device__ __forceinline__ void bulk_g2s_stream(uint32_t dst, const void* src, uint32_t bytes, uint32_t mbar, uint64_t pol) {
    asm volatile("cp.async.bulk.shared::cluster.global.mbarrier::complete_tx::bytes.L2::cache_hint [%0], [%1], %2, [%3], %4;"
                 ::"r"(dst), "l"(src), "r"(bytes), "r"(mbar), "l"(pol) : "memory");
}
__device__ __forceinline__ void bulk_g2s(uint32_t dst, const void* src, uint32_t bytes, uint32_t mbar) {
    asm volatile("cp.async.bulk.shared::cluster.global.mbarrier::complete_tx::bytes [%0], [%1], %2, [%3];"
                 ::"r"(dst), "l"(src), "r"(bytes), "r"(mbar) : "memory");
}
__device__ __forceinline__ void cp16(uint32_t dst, const void* src) {
    asm volatile("cp.async.cg.shared.global [%0], [%1], 16;" ::"r"(dst), "l"(src) : "memory");
}
__device__ __forceinline__ float bf_lo(uint32_t u) { return __uint_as_float(u << 16); }
__device__ __forceinline__ float bf_hi(uint32_t u) { return __uint_as_float(u & 0xffff0000u); }
__device__ __forceinline__ float bf_round(float x) { return __bfloat162float(__float2bfloat16_rn(x)); }
__device__ __forceinline__ uint32_t ld_pair(const __nv_bfloat16* p) {
    return __ldg(reinterpret_cast<const uint32_t*>(p));
}
__device__ __forceinline__ unsigned int ld_relaxed(const unsigned int* p) {
    unsigned int v;
    asm volatile("ld.relaxed.gpu.global.u32 %0, [%1];" : "=r"(v) : "l"(p) : "memory");
    return v;
}
__device__ __forceinline__ unsigned long long pack_rec(float a, float b, uint32_t tag) {
    const uint32_t x = (__float_as_uint(a) & ~15u) | (tag & 15u), y = (__float_as_uint(b) & ~15u) | (tag >> 4);
    return ((unsigned long long)y << 32) | x;
}
__device__ __forceinline__ void st_rec(unsigned long long* p, float a, float b, uint32_t tag) {
    asm volatile("st.relaxed.gpu.global.b64 [%0], %1;" ::"l"(p), "l"(pack_rec(a, b, tag)) : "memory");
}
__device__ __forceinline__ float rec_lo(unsigned long long w) { return __uint_as_float((uint32_t)w & ~15u); }
__device__ __forceinline__ float rec_hi(unsigned long long w) { return __uint_as_float((uint32_t)(w >> 32) & ~15u); }
__device__ __forceinline__ unsigned long long ld_rec1(const unsigned long long* p) {
    unsigned long long x;
    asm volatile("ld.relaxed.gpu.global.b64 %0, [%1];" : "=l"(x) : "l"(p) : "memory");
    return x;
}
__device__ __forceinline__ void ld_rec2(const unsigned long long* p, unsigned long long& x, unsigned long long& y) {
    asm volatile("ld.relaxed.gpu.global.v2.b64 {%0, %1}, [%2];" : "=l"(x), "=l"(y) : "l"(p) : "memory");
}
__device__ __forceinline__ uint32_t rec_bad(unsigned long long w, uint32_t tlo, uint32_t thi) {
    return (((uint32_t)w ^ tlo) | ((uint32_t)(w >> 32) ^ thi)) & 15u;
}
__device__ __forceinline__ void st_ml(unsigned long long* p, float m, float l, uint32_t tag) {
    const uint32_t y = ((__float_as_uint(l) + 0x80u) & ~0xffu) | tag;
    asm volatile("st.relaxed.gpu.global.b64 [%0], %1;" ::"l"(p), "l"(((unsigned long long)y << 32) | __float_as_uint(m)) : "memory");
}
__device__ __forceinline__ uint32_t ml_bad(unsigned long long w, uint32_t tag) { return ((uint32_t)(w >> 32) ^ tag) & 0xffu; }
__device__ __forceinline__ float ml_m(unsigned long long w) { return __uint_as_float((uint32_t)w); }
__device__ __forceinline__ float ml_l(unsigned long long w) { return __uint_as_float((uint32_t)(w >> 32) & ~0xffu); }
__device__ __forceinline__ float warp_max(float v) {
    const int b = __float_as_int(v);
    const int k = __reduce_max_sync(0xffffffffu, b ^ ((b >> 31) & 0x7fffffff));
    return __int_as_float(k ^ ((k >> 31) & 0x7fffffff));
}
__device__ __forceinline__ uint32_t round_tag(unsigned int epoch, int r) {
    constexpr unsigned kUses = (kRounds + kPR - 1) / kPR;
    return (epoch * kUses + (unsigned)(r / kPR)) % 255u + 1u;
}

__device__ __forceinline__ void rotate_q(uint32_t* qrow, int p, uint32_t c_lo, uint32_t c_hi, uint32_t s_lo, uint32_t s_hi) {
    const uint32_t lo = qrow[p], hi = qrow[p + 48];
    const float a0 = bf_round(bf_lo(lo) * bf_lo(c_lo)) + bf_round(-bf_lo(hi) * bf_lo(s_lo));
    const float a1 = bf_round(bf_hi(lo) * bf_hi(c_lo)) + bf_round(-bf_hi(hi) * bf_hi(s_lo));
    const float b0 = bf_round(bf_lo(hi) * bf_lo(c_hi)) + bf_round(bf_lo(lo) * bf_lo(s_hi));
    const float b1 = bf_round(bf_hi(hi) * bf_hi(c_hi)) + bf_round(bf_hi(lo) * bf_hi(s_hi));
    const __nv_bfloat162 ua = __floats2bfloat162_rn(a0, a1), ub = __floats2bfloat162_rn(b0, b1);
    qrow[p] = *reinterpret_cast<const uint32_t*>(&ua);
    qrow[p + 48] = *reinterpret_cast<const uint32_t*>(&ub);
}
__device__ __forceinline__ int deferred_to(int blk, int r) {
    return (unsigned)(r - kDef0) < (unsigned)kFHeads ? (blk - kF * (r - kDef0)) & (kFHeads - 1) : kF;
}

struct Scalars { const __nv_bfloat16* p[4]; };

__global__ void __launch_bounds__(kThreads, 1)
attn_kernel(const __grid_constant__ Scalars scal, const int* __restrict__ qk, const __nv_bfloat16* __restrict__ kcos,
            const __nv_bfloat16* __restrict__ ksin, const int* __restrict__ qv, const __nv_bfloat16* __restrict__ q,
            const __nv_bfloat16* __restrict__ qcos, const __nv_bfloat16* __restrict__ qsin,
            __nv_bfloat16* __restrict__ out, const __grid_constant__ CUtensorMap tmv) {
    extern __shared__ __align__(128) unsigned char smem[];
    const int warp = threadIdx.x >> 5, lane = threadIdx.x & 31;
    const uint32_t full0 = s2u(smem + kOffBar), empty0 = full0 + 2 * kNS * 8;
    const uint32_t sfull = empty0 + 2 * kNS * 8, sempty = sfull + 16, mxbar = sempty + 16, fine = mxbar + 16;
    volatile unsigned int* s_misc = reinterpret_cast<volatile unsigned int*>(smem + kOffMisc);
    uint64_t pol = 0;

    if (threadIdx.x == kCW * 32 && blockIdx.x < kStream) {
        const int m = blockIdx.x % kSlots;
        const uint32_t sm0 = s2u(smem);
        asm volatile("cp.async.bulk.prefetch.L2.global [%0], %1;"
                     ::"l"(scal.p[blockIdx.x & 3] + (blockIdx.x >> 2) * (kNH * kS * 4 / kStream)), "n"(kNH * kS * 4 / kStream * 2) : "memory");
        for (int i = 0; i < 2 * kNS; i++) mbar_init(full0 + 8 * i, 1);
        asm volatile("fence.mbarrier_init.release.cluster;" ::: "memory");
        asm volatile("createpolicy.fractional.L2::evict_first.b64 %0, 1.0;" : "=l"(pol));
        const int* k0 = qk + (size_t)(blockIdx.x / kSlots * kS + m * kHRows) * kD;
#pragma unroll
        for (int h = 0; h < 2; h++) {
            mbar_expect(full0 + 16 + 8 * h, kHalf);
            bulk_g2s_stream(sm0 + kChunk + h * kHalf, k0 + h * (kS / 2 * kD), kHalf, full0 + 16 + 8 * h, pol);
        }
#pragma unroll
        for (int h = 0; h < 2; h++) {
            mbar_expect(full0 + 8 * h, kHalf);
            bulk_g2s(sm0 + h * kHalf, kcos + (h * (kS / 2) + m * kHRows) * kD, kHalf / 2, full0 + 8 * h);
            bulk_g2s(sm0 + h * kHalf + kHalf / 2, ksin + (h * (kS / 2) + m * kHRows) * kD, kHalf / 2, full0 + 8 * h);
        }
#pragma unroll
        for (int h = 0; h < 2; h++) {
            mbar_expect(full0 + 32 + 8 * h, kHalf);
            bulk_g2s_stream(sm0 + 2 * kChunk + h * kHalf, k0 + (kTeams * kS + h * (kS / 2)) * kD, kHalf, full0 + 32 + 8 * h, pol);
        }
    }

    if (blockIdx.x >= kStream) {
        const int team = blockIdx.x - kStream;
        if (threadIdx.x == 0) s_misc[0] = ld_relaxed(&g_epoch);
        __syncthreads();
        if (threadIdx.x == 0 && atomicAdd(&g_arrive, 1u) == kGrid - 1) { g_arrive = 0u; g_epoch = s_misc[0] + 1u; }
        if (warp >= 3 * kMG) return;
        const int grp = warp / 3, t = threadIdx.x - grp * 96;
        constexpr int kRecBytes = kSlots * kRecWords * 8;
        if (t == 0) {
            mbar_init(s2u(smem + kOffBar) + grp * 8, 1);
            asm volatile("fence.mbarrier_init.release.cluster;" ::: "memory");
        }
        asm volatile("bar.sync %0, 96;" ::"r"(3 + grp) : "memory");
        for (int r = grp; r < kRounds; r += kMG) {
            const int g = r % kMG;
            const int tt = threadIdx.x - g * 96, qd = tt % 48, half = tt / 48;
            const uint32_t tag = round_tag(s_misc[0], r);
            const uint32_t tlo = tag & 15u, thi = tag >> 4;
            const unsigned long long* rec = g_rec + ((size_t)(r % kPR) * kStream + team * kSlots) * kRecWords;
            unsigned long long ml, x[16], y[16];
            {
                const unsigned long long* buf = reinterpret_cast<const unsigned long long*>(smem + g * kRecBytes);
                const uint32_t mb = s2u(smem + kOffBar) + g * 8;
                if (tt < 32) {
                    const int want = r == kRounds - 1 ? kQuick : kSlots;
                    for (int i2 = 0;; i2++) {
                        ml = ld_rec1(rec + lane * kRecWords + 96);
                        if (__popc(__ballot_sync(0xffffffffu, ml_bad(ml, tag) == 0)) >= want) break;
                        if (i2 > kSpin) __trap();
                        __nanosleep(kSleep);
                    }
                    if (tt == 0) {
                        mbar_expect(mb, kRecBytes);
                        bulk_g2s(s2u(buf), rec, kRecBytes, mb);
                    }
                }
                mbar_wait(mb, (r / kMG) & 1);
                ml = buf[lane * kRecWords + 96];
#pragma unroll
                for (int i = 0; i < 16; i++) {
                    const ulonglong2 u = *reinterpret_cast<const ulonglong2*>(buf + (half * 16 + i) * kRecWords + 2 * qd);
                    x[i] = u.x; y[i] = u.y;
                }
                const unsigned long long* po = rec + half * 16 * kRecWords + 2 * qd;
                for (int it = 0;; it++) {
                    uint32_t any = ml_bad(ml, tag);
                    if (any) ml = ld_rec1(rec + lane * kRecWords + 96);
#pragma unroll
                    for (int i = 0; i < 16; i++) {
                        const uint32_t bad = rec_bad(x[i], tlo, thi) | rec_bad(y[i], tlo, thi);
                        if (bad) ld_rec2(po + i * kRecWords, x[i], y[i]);
                        any |= bad;
                    }
                    if (__all_sync(0xffffffffu, any == 0)) break;
                    if (it > kSpin) __trap();
                }
            }
            const float M = ml_m(ml);
            const float MM = warp_max(M);
            const float w = exp2f(M - MM);
            float LL = w * ml_l(ml);
#pragma unroll
            for (int o = 16; o > 0; o >>= 1) LL += __shfl_xor_sync(0xffffffffu, LL, o);
            float4 a = make_float4(0.f, 0.f, 0.f, 0.f);
#pragma unroll
            for (int i = 0; i < 16; i++) {
                const float wi = __shfl_sync(0xffffffffu, w, half * 16 + i);
                a.x = fmaf(wi, rec_lo(x[i]), a.x);
                a.y = fmaf(wi, rec_hi(x[i]), a.y);
                a.z = fmaf(wi, rec_lo(y[i]), a.z);
                a.w = fmaf(wi, rec_hi(y[i]), a.w);
            }
            float* rb = reinterpret_cast<float*>(smem + kMG * kRecBytes) + (2 * g + ((r / kMG) & 1)) * kD + 4 * qd;
            if (half == 1) *reinterpret_cast<float4*>(rb) = a;
            asm volatile("bar.sync %0, 96;" ::"r"(3 + g) : "memory");
            if (half == 0) {
                const float4 u = *reinterpret_cast<float4*>(rb);
                if ((unsigned)(r - kDef0) < (unsigned)kFHeads) {
                    unsigned long long* pre = g_pre + (size_t)(team * kFHeads + r - kDef0) * kRecWords;
                    const uint32_t ptag = s_misc[0] % 255u + 1u;
                    st_rec(pre + 2 * qd, a.x + u.x, a.y + u.y, ptag);
                    st_rec(pre + 2 * qd + 1, a.z + u.z, a.w + u.w, ptag);
                    if (qd == 0) st_ml(pre + 96, MM, LL, ptag);
                } else {
                    const float inv = __fdividef(1.0f, LL);
                    const __nv_bfloat162 o0 = __floats2bfloat162_rn((a.x + u.x) * inv, (a.y + u.y) * inv);
                    const __nv_bfloat162 o1 = __floats2bfloat162_rn((a.z + u.z) * inv, (a.w + u.w) * inv);
                    uint2 ov;
                    ov.x = *reinterpret_cast<const uint32_t*>(&o0);
                    ov.y = *reinterpret_cast<const uint32_t*>(&o1);
                    *reinterpret_cast<uint2*>(out + (size_t)(kTeams * r + team) * kD + 4 * qd) = ov;
                }
            }
            if (tt == 95)
                asm volatile("st.relaxed.gpu.global.u32 [%0], %1;" ::"l"(&g_mdone[(team * kMG + g) * 32]), "r"(s_misc[0] * kRounds + r + 1) : "memory");
        }
        return;
    }

    const int m = blockIdx.x % kSlots, team = blockIdx.x / kSlots;
    const int row0 = m * kHRows;

    if (warp == kCW) {
        unsigned int epoch = 0;
        const size_t off0 = ((size_t)team * kS + row0) * kD;
        const uint32_t sm0 = s2u(smem);
        if (lane == 0) {
            epoch = ld_relaxed(&g_epoch);
            s_misc[0] = epoch;
        }
        __syncwarp();
        asm volatile("bar.sync 2, %0;" ::"n"(kThreads) : "memory");
        if (lane == 0) {
            unsigned int cum = epoch * (kStream * (4 * kRounds - 2)) + 4 * kStream;
            unsigned int seen = cum - 4 * kStream;
            unsigned int need = seen;
            int use0 = kNS, use1 = kNS;
            const unsigned int* prog = &g_prog;
            const int* kp = qk + off0;
            const int* vp = qv + off0;
            for (int ph2 = 4; ph2 < 2 * (2 * kRounds + kF); ph2++) {
                unsigned int v = seen;
                asm volatile("{\n.reg .pred p;\nsetp.lt.s32 p, %2, 0;\n@p ld.relaxed.gpu.global.u32 %0, [%1];\n}"
                             : "+r"(v) : "l"(prog), "r"(seen - need) : "memory");
                const int p = ph2 >> 1, h = ph2 & 1;
                const bool isv = (p & 1) == 0 || p == 2 * kRounds - 1;
                const int r = p == 2 * kRounds - 1 ? kRounds - 1 : isv ? (p >> 1) - 1 : (p + 1) >> 1;
                const uint32_t dm = (isv && (unsigned)(r - kDef0) < (unsigned)kFHeads)
                                        ? ((((1u << kF) - 1) * 0x101u << ((kF * (r - kDef0)) & (kFHeads - 1))) >> (8 + 4 * h)) & 15u : 0u;
                cum += kStream - (kStream / 4) * __popc(dm);
                const unsigned int need_next = cum - max(kRampEnd - (ph2 + 1), 0) * kRampStep -
                    ((unsigned)(ph2 + 1 - (4 * kDef0 + 4)) < (unsigned)(4 * kFHeads + 2) ? kLeadDef : kLead);
                const bool skip = (dm >> (m / 8)) & 1;
                const int u = h ? use1 : use0;
                const int slot = u >= kNS ? u - kNS : u;
                const uint32_t dst = sm0 + slot * kChunk + h * kHalf, fullb = full0 + 16 * slot + 8 * h;
                const int* src = (isv ? vp : kp) + (size_t)(r * kTeams * kS + h * (kS / 2)) * kD;
                if (!skip) {
                    const int un = u + 1 == 2 * kNS ? 0 : u + 1;
                    if (h) use1 = un; else use0 = un;
                    mbar_wait(fullb + 2 * kNS * 8, u >= kNS ? 0 : 1);
                    if (p < 2 * kRounds) mbar_expect(fullb, kHalf);
                }
                asm volatile("" ::"r"(need_next), "l"(src), "r"(dst) : "memory");
                seen = v;
                if (!skip)
                    for (int it = 0; (int)(seen - need) < 0; it++) {
                        seen = ld_relaxed(prog);
                        if (it > kSpin) __trap();
                    }
                need = need_next;
                if (p >= 2 * kRounds || skip) {
                    const int hi = m / kFG;
                    const int row = (kTeams * (kDef0 + hi) + team) * kS + ((kF * hi + p - 2 * kRounds) & (kFHeads - 1)) * kFRows + h * (kFRows / 2);
                    const uint32_t fb = fine + 8 * (kFBoxes / 2) * (ph2 - 4 * kRounds);
#pragma unroll 1
                    for (int w = 0; w < kFBoxes / 2; w++)
                        asm volatile("{\n.reg .pred p;\nsetp.ne.u32 p, %6, 0;\n"
                                     "@p cp.async.bulk.tensor.2d.shared::cluster.global.tile.mbarrier::complete_tx::bytes.L2::cache_hint [%0], [%1, {%2, %3}], [%4], %5;\n}"
                                     ::"r"(dst + w * (kChunk / kFBoxes)), "l"(&tmv), "r"((m % kFG) * kFW), "r"(row + w * (kFRows / kFBoxes)),
                                       "r"(fb + 8 * w), "l"(pol), "r"((uint32_t)!skip) : "memory");
                } else {
                    bulk_g2s_stream(dst, src, kHalf, fullb, pol);
                }
            }
        }
    } else if (warp == kCW + 1) {
        {
            if (lane < 2 * kNS + 6) mbar_init(empty0 + 8 * lane, lane < 2 * kNS ? kCW / 2 : (lane >= 2 * kNS + 2 && lane < 2 * kNS + 4) ? 1 : kCW);
            asm volatile("fence.mbarrier_init.release.cluster;" ::: "memory");
        }
        asm volatile("bar.sync 2, %0;" ::"n"(kThreads) : "memory");
        const unsigned int epoch = s_misc[0];
        if (lane == 0 && atomicAdd(&g_arrive, 1u) == kGrid - 1) { g_arrive = 0u; g_epoch = epoch + 1u; }
        {
            const uint32_t sm0 = s2u(smem);
            const __nv_bfloat16* src = scal.p[lane >> 3] + (size_t)team * kS + row0 + (lane & 4) * (kS / 8) + (lane & 3) * 8;
            const __nv_bfloat16* qs = q + team * kD + lane * 8;
#pragma unroll 1
            for (int r = kEarly; r < kRounds; r++) {
                cp16(sm0 + kOffScal + r * 512 + lane * 16, src + (size_t)r * (kTeams * kS));
                if (lane < 24) cp16(sm0 + kOffQ + r * (kD * 2) + lane * 16, qs + r * (kTeams * kD));
                if (r == 2 * kEarly - 1 || r == kRounds - 1) asm volatile("cp.async.commit_group;" ::: "memory");
            }
        }
        uint32_t cs[2][4];
#pragma unroll
        for (int i = 0; i < 2; i++) {
            const int p = (lane + 32 * i) % 48;
            cs[i][0] = ld_pair(qcos + 2 * p); cs[i][1] = ld_pair(qcos + 2 * p + 96);
            cs[i][2] = ld_pair(qsin + 2 * p); cs[i][3] = ld_pair(qsin + 2 * p + 96);
        }
        asm volatile("cp.async.wait_group 1;" ::: "memory");
        __syncwarp();
        for (int r = 0; r < kRounds; r++) {
            const float* sc = reinterpret_cast<const float*>(smem + kOffSc) + (r & 1) * (kCW * kScStride);
            const uint32_t tag = round_tag(epoch, r);
            unsigned long long* rec = g_rec + ((size_t)(r % kPR) * kStream + team * kSlots + m) * kRecWords;
            if (r >= kEarly && r < kEarly + kF * kFBoxes && lane == 0) {
                mbar_init(fine + 8 * (r - kEarly), 1);
                asm volatile("fence.mbarrier_init.release.cluster;" ::: "memory");
                mbar_expect(fine + 8 * (r - kEarly), kChunk / kFBoxes);
                asm volatile("fence.proxy.async.shared::cta;" ::: "memory");
            }
            if (r == kPrep + m / 2) {
                const unsigned long long* pre = g_pre + (size_t)(team * kFHeads + m / kFG) * kRecWords;
                const unsigned long long* lgp = g_lg + (size_t)(team * kFHeads + m / kFG) * (kF * kFRows);
                const uint32_t ptag = epoch % 255u + 1u;
                unsigned long long ml, po;
                for (int it = 0;; it++) {
                    ml = ld_rec1(pre + 96);
                    po = ld_rec1(pre + (m % kFG) * (kFW / 2) + lane % (kFW / 2));
                    if (!(ml_bad(ml, ptag) | rec_bad(po, ptag & 15u, ptag >> 4))) break;
                    if (it > kSpin) __trap();
                }
                const float inv = 1.0f / ml_l(ml);
                if (lane < kFW / 2) {
                    reinterpret_cast<float*>(smem + kOffFin)[lane] = rec_lo(po) * inv;
                    reinterpret_cast<float*>(smem + kOffFin)[kFW / 2 + lane] = rec_hi(po) * inv;
                }
#pragma unroll 1
                for (int c = 0; c < kF; c++) {
                    unsigned long long u[8];
                    for (int it = 0;; it++) {
                        uint32_t bad = 0;
#pragma unroll
                        for (int k = 0; k < 8; k++) {
                            u[k] = ld_rec1(lgp + c * kFRows + 32 * k + lane);
                            bad |= ml_bad(u[k], ptag);
                        }
                        if (!bad) break;
                        if (it > kSpin) __trap();
                    }
#pragma unroll
                    for (int k = 0; k < 8; k++)
                        reinterpret_cast<float*>(smem + kOffW)[c * kFRows + 32 * k + lane] = ml_l(u[k]) * exp2f(ml_m(u[k]) - ml_m(ml)) * inv;
                }
                __syncwarp();
            }
            if (r == kRounds - 3 && lane == 0) asm volatile("prefetch.tensormap [%0];" ::"l"(&tmv) : "memory");
            if (r == kEarly) {
                asm volatile("cp.async.wait_all;" ::: "memory");
                __syncwarp();
            }
            if (r + kEarly < kRounds) {
                uint32_t* qrow = reinterpret_cast<uint32_t*>(smem + kOffQ + (r + kEarly) * (kD * 2));
                rotate_q(qrow, lane, cs[0][0], cs[0][1], cs[0][2], cs[0][3]);
                if (lane < 16) rotate_q(qrow, lane + 32, cs[1][0], cs[1][1], cs[1][2], cs[1][3]);
            }
            if (r >= kPR) {
                const unsigned int* mdone = &g_mdone[(team * kMG + r % kMG) * 32];
                const unsigned int need = epoch * kRounds + r - kPR + 1;
                for (int it = 0; (int)(ld_relaxed(mdone) - need) < 0; it++)
                    if (it > kSpin) __trap();
            }
            mbar_wait(sfull + 8 * (r & 1), (r >> 1) & 1);
            const float M = sc[0];
            float L = lane < kCW ? sc[lane * kScStride + 1] : 0.f;
            float acc[2][6];
#pragma unroll
            for (int ww = 0; ww < kCW; ww++) {
#pragma unroll
                for (int j = 0; j < 3; j++) {
                    const float2 t = *reinterpret_cast<const float2*>(sc + ww * kScStride + 4 + 64 * j + 2 * lane);
                    acc[ww & 1][2 * j] = ww < 2 ? t.x : acc[ww & 1][2 * j] + t.x;
                    acc[ww & 1][2 * j + 1] = ww < 2 ? t.y : acc[ww & 1][2 * j + 1] + t.y;
                }
                if ((ww & 3) == 3 && ww < 15) L += __shfl_xor_sync(0xffffffffu, L, 8 >> (ww >> 2));
            }
            L += __shfl_xor_sync(0xffffffffu, L, 1);
#pragma unroll
            for (int j = 0; j < 3; j++)
                st_rec(rec + 32 * j + lane, acc[0][2 * j] + acc[1][2 * j], acc[0][2 * j + 1] + acc[1][2 * j + 1], tag);
            if (lane == 0) st_ml(rec + 96, M, L, tag);
            __syncwarp();
            if (lane == 0) mbar_arrive(sempty + 8 * (r & 1));
        }
    } else {
        int dp[3];
#pragma unroll
        for (int j = 0; j < 3; j++) dp[j] = (64 * j + 2 * lane + 96) % kD;
        {
            const uint32_t sm0 = s2u(smem);
            if (warp < kEarly) {
                cp16(sm0 + kOffScal + threadIdx.x * 16, scal.p[lane >> 3] + (size_t)(kTeams * warp + team) * kS + row0 + (lane & 4) * (kS / 8) + (lane & 3) * 8);
            } else if (warp < 2 * kEarly && lane < 24) {
                cp16(sm0 + kOffQ + (warp - kEarly) * (kD * 2) + lane * 16, q + (size_t)(kTeams * (warp - kEarly) + team) * kD + lane * 8);
            }
            asm volatile("cp.async.commit_group;" ::: "memory");
        }
        const int p = threadIdx.x % 48, g = threadIdx.x / 48;
        const uint32_t c_lo = ld_pair(qcos + 2 * p), c_hi = ld_pair(qcos + 2 * p + 96);
        const uint32_t s_lo = ld_pair(qsin + 2 * p), s_hi = ld_pair(qsin + 2 * p + 96);
        float kc[kR][6], ks[kR][6];
        asm volatile("bar.sync 2, %0;" ::"n"(kThreads) : "memory");
        const int half = warp / (kCW / 2);
        const uint32_t fullh = full0 + 8 * half, emptyh = empty0 + 8 * half;
        mbar_wait(fullh, 0);
#pragma unroll
        for (int i = 0; i < kR; i++) {
            const unsigned char* cb = smem + half * (kHalf / 2) + (warp * kR + i) * (kD * 2);
#pragma unroll
            for (int j = 0; j < 3; j++) {
                const uint32_t uc = *reinterpret_cast<const uint32_t*>(cb + 128 * j + 4 * lane);
                const uint32_t us = *reinterpret_cast<const uint32_t*>(cb + kHalf / 2 + 2 * dp[j]);
                kc[i][2 * j] = bf_lo(uc); kc[i][2 * j + 1] = bf_hi(uc);
                const float sg = (j == 0 || (j == 1 && lane < 16)) ? 1.f : -1.f;
                ks[i][2 * j] = sg * bf_lo(us); ks[i][2 * j + 1] = sg * bf_hi(us);
            }
        }
        __syncwarp();
        if (lane == 0) mbar_arrive(emptyh);
        asm volatile("cp.async.wait_group 0;" ::: "memory");
        asm volatile("bar.sync 1, %0;" ::"n"(kCW * 32) : "memory");
        if (g < kEarly) rotate_q(reinterpret_cast<uint32_t*>(smem + kOffQ + g * (kD * 2)), p, c_lo, c_hi, s_lo, s_hi);
        asm volatile("bar.sync 1, %0;" ::"n"(kCW * 32) : "memory");
        const float scale_log2e = 1.4426950408889634f * rsqrtf((float)kD);
        float* my0 = reinterpret_cast<float*>(smem + kOffSc) + warp * kScStride;

        float* s_max = reinterpret_cast<float*>(smem + kOffMax);
        int slot = 1;
        uint32_t ph = 0;
        float lgc[kR] = {0.f, 0.f, 0.f, 0.f};
        for (int it = 0; it <= kRounds; it++) {
            float lg[kR];
            if (it < kRounds) {
                float qa[6], qb[6];
#pragma unroll
                for (int j = 0; j < 3; j++) {
                    const uint32_t qo = *reinterpret_cast<const uint32_t*>(smem + kOffQ + it * (kD * 2) + 2 * (64 * j + 2 * lane));
                    const uint32_t qp = *reinterpret_cast<const uint32_t*>(smem + kOffQ + it * (kD * 2) + 2 * dp[j]);
                    qa[2 * j] = bf_lo(qo); qa[2 * j + 1] = bf_hi(qo);
                    qb[2 * j] = bf_lo(qp); qb[2 * j + 1] = bf_hi(qp);
                }
                const unsigned char* sp = smem + kOffScal + it * (4 * kRows * 2) + warp * (kR * 2);
                const uint2 uks = *reinterpret_cast<const uint2*>(sp);
                const uint2 ukz = *reinterpret_cast<const uint2*>(sp + kRows * 2);
                const float kz[4] = {bf_lo(ukz.x), bf_hi(ukz.x), bf_lo(ukz.y), bf_hi(ukz.y)};
                const float sk[4] = {bf_lo(uks.x), bf_hi(uks.x), bf_lo(uks.y), bf_hi(uks.y)};
                mbar_wait(fullh + 16 * slot, ph);
                if ((threadIdx.x & 255) == 0) asm volatile("red.relaxed.gpu.global.add.u32 [%0], 1;" ::"l"(&g_prog) : "memory");
                const unsigned char* kb = smem + slot * kChunk + warp * (kR * kRowBytes) + lane * 8;
#pragma unroll
                for (int i = 0; i < kR; i++) {
                    float dot = 0.f;
#pragma unroll
                    for (int j = 0; j < 3; j++) {
                        const int2 kk = *reinterpret_cast<const int2*>(kb + i * kRowBytes + 256 * j);
                        const float e0 = qa[2 * j] * kc[i][2 * j] + qb[2 * j] * ks[i][2 * j];
                        const float e1 = qa[2 * j + 1] * kc[i][2 * j + 1] + qb[2 * j + 1] * ks[i][2 * j + 1];
                        dot = fmaf((float)kk.x - kz[i], e0, dot);
                        dot = fmaf((float)kk.y - kz[i], e1, dot);
                    }
                    lg[i] = dot;
                }
                __syncwarp();
                if (lane == 0) mbar_arrive(emptyh + 16 * slot);
                if (++slot == kNS) { slot = 0; ph ^= 1; }
#pragma unroll
                for (int o = 16; o > 0; o >>= 1) {
#pragma unroll
                    for (int i = 0; i < kR; i++) lg[i] += __shfl_xor_sync(0xffffffffu, lg[i], o);
                }
                float mw = -INFINITY;
#pragma unroll
                for (int i = 0; i < kR; i++) {
                    lg[i] = lg[i] * sk[i] * scale_log2e;
                    mw = fmaxf(mw, lg[i]);
                }
                if (lane == 0) {
                    s_max[(it & 3) * kCW + warp] = mw;
                    mbar_arrive(mxbar + 8 * (it & 1));
                }
            }
            if (it > 0) {
                const int r = it - 1;
                float* my = my0 + (r & 1) * (kCW * kScStride);
                const int df = deferred_to(4 * half + m / 8, r);
                const unsigned char* sp = smem + kOffScal + r * (4 * kRows * 2) + warp * (kR * 2);
                const uint2 uvs = *reinterpret_cast<const uint2*>(sp + 2 * kRows * 2);
                const uint2 uvz = *reinterpret_cast<const uint2*>(sp + 3 * kRows * 2);
                const float vz[4] = {bf_lo(uvz.x), bf_hi(uvz.x), bf_lo(uvz.y), bf_hi(uvz.y)};
                const float sv[4] = {bf_lo(uvs.x), bf_hi(uvs.x), bf_lo(uvs.y), bf_hi(uvs.y)};
                mbar_wait(mxbar + 8 * (r & 1), (r >> 1) & 1);
                float M;
                {
                    const float4* pm4 = reinterpret_cast<const float4*>(s_max + (r & 3) * kCW);
                    const float4 m0 = pm4[0], m1 = pm4[1], m2 = pm4[2], m3 = pm4[3];
                    M = fmaxf(fmaxf(fmaxf(fmaxf(m0.x, m0.y), fmaxf(m0.z, m0.w)), fmaxf(fmaxf(m1.x, m1.y), fmaxf(m1.z, m1.w))),
                              fmaxf(fmaxf(fmaxf(m2.x, m2.y), fmaxf(m2.z, m2.w)), fmaxf(fmaxf(m3.x, m3.y), fmaxf(m3.z, m3.w))));
                }
                float lw = 0.f, cz = 0.f, pv[kR];
#pragma unroll
                for (int i = 0; i < kR; i++) {
                    const float p = exp2f(lgc[i] - M);
                    lw += p;
                    pv[i] = p * sv[i];
                    cz = fmaf(pv[i], vz[i], cz);
                }
                mbar_wait(sempty + 8 * (r & 1), ((r >> 1) & 1) ^ 1);
                if (lane == 0) { my[0] = M; my[1] = lw; }
                float acc[6] = {-cz, -cz, -cz, -cz, -cz, -cz};
                if (df < kF) {
                    if (lane < kR)
                        st_ml(g_lg + ((team * kFHeads + r - kDef0) * kF + df) * kFRows + (m % 8) * kHRows + (warp % 8) * kR + lane, M,
                              lane == 0 ? pv[0] : lane == 1 ? pv[1] : lane == 2 ? pv[2] : pv[3], s_misc[0] % 255u + 1u);
                } else {
                    mbar_wait(fullh + 16 * slot, ph);
                    if ((threadIdx.x & 255) == 0) asm volatile("red.relaxed.gpu.global.add.u32 [%0], 1;" ::"l"(&g_prog) : "memory");
                    const unsigned char* vb = smem + slot * kChunk + warp * (kR * kRowBytes) + lane * 8;
#pragma unroll
                    for (int i = 0; i < kR; i++) {
#pragma unroll
                        for (int j = 0; j < 3; j++) {
                            const int2 vv = *reinterpret_cast<const int2*>(vb + i * kRowBytes + 256 * j);
                            acc[2 * j] = fmaf(pv[i], (float)vv.x, acc[2 * j]);
                            acc[2 * j + 1] = fmaf(pv[i], (float)vv.y, acc[2 * j + 1]);
                        }
                    }
                    __syncwarp();
                    if (lane == 0) mbar_arrive(emptyh + 16 * slot);
                    if (++slot == kNS) { slot = 0; ph ^= 1; }
                }
#pragma unroll
                for (int j = 0; j < 3; j++)
                    *reinterpret_cast<float2*>(my + 4 + 64 * j + 2 * lane) = make_float2(acc[2 * j], acc[2 * j + 1]);
                __syncwarp();
                if (lane == 0) mbar_arrive(sfull + 8 * (r & 1));
            }
#pragma unroll
            for (int i = 0; i < kR; i++) lgc[i] = lg[i];
        }
        {
            const int cp = lane < kFW / 2 ? lane : 0;
            const int ft = threadIdx.x < kFW ? threadIdx.x : 0;
            const float fin = reinterpret_cast<const float*>(smem + kOffFin)[ft];
            __nv_bfloat16* op = out + (size_t)(kTeams * (kDef0 + m / kFG) + team) * kD + (m % kFG) * kFW + 2 * (ft % (kFW / 2)) + ft / (kFW / 2);
            float a0 = 0.f, a1 = 0.f, b0 = 0.f, b1 = 0.f;
#pragma unroll 1
            for (int f = 0; f < kF; f++) {
                const float* sw = reinterpret_cast<const float*>(smem + kOffW) + f * kFRows + (warp >> 2) * 16 + (warp & 3) * 4;
                const unsigned char* vb = smem + slot * kChunk + ((warp >> 2) * 16 + (warp & 3) * 4) * (kFW * 4) + cp * 8;
                const uint32_t fb = fine + (f * kFBoxes + (warp >> 2)) * 8;
                float* part = reinterpret_cast<float*>(smem + kOffPart) + f * (kFW * kPartStride);
                float4 w[4];
#pragma unroll
                for (int k = 0; k < 4; k++) w[k] = *reinterpret_cast<const float4*>(sw + 64 * k);
#pragma unroll
                for (int k = 0; k < 4; k++) {
                    mbar_wait(fb + 32 * k, 0);
                    if ((k & 1) && threadIdx.x == kCW * 32 - 32 && f < kF - 1) asm volatile("red.relaxed.gpu.global.add.u32 [%0], 1;" ::"l"(&g_prog) : "memory");
                    const int2 v0 = *reinterpret_cast<const int2*>(vb + k * (64 * kFW * 4));
                    const int2 v1 = *reinterpret_cast<const int2*>(vb + k * (64 * kFW * 4) + kFW * 4);
                    const int2 v2 = *reinterpret_cast<const int2*>(vb + k * (64 * kFW * 4) + 2 * kFW * 4);
                    const int2 v3 = *reinterpret_cast<const int2*>(vb + k * (64 * kFW * 4) + 3 * kFW * 4);
                    a0 = fmaf(w[k].x, (float)v0.x, a0); a1 = fmaf(w[k].x, (float)v0.y, a1);
                    b0 = fmaf(w[k].y, (float)v1.x, b0); b1 = fmaf(w[k].y, (float)v1.y, b1);
                    a0 = fmaf(w[k].z, (float)v2.x, a0); a1 = fmaf(w[k].z, (float)v2.y, a1);
                    b0 = fmaf(w[k].w, (float)v3.x, b0); b1 = fmaf(w[k].w, (float)v3.y, b1);
                }
                if (lane < kFW / 2) {
                    part[lane * kPartStride + warp] = a0 + b0;
                    part[(kFW / 2 + lane) * kPartStride + warp] = a1 + b1;
                }
                if (warp >= 2) {
                    asm volatile("bar.arrive %0, %1;" ::"r"(3 + f), "n"(kCW * 32) : "memory");
                } else {
                    asm volatile("bar.sync %0, %1;" ::"r"(3 + f), "n"(kCW * 32) : "memory");
                    const float4* ps = reinterpret_cast<const float4*>(part + ft * kPartStride);
                    const float4 p0 = ps[0], p1 = ps[1], p2 = ps[2], p3 = ps[3];
                    const float sum = (((p0.x + p0.y) + (p0.z + p0.w)) + ((p1.x + p1.y) + (p1.z + p1.w))) +
                                      (((p2.x + p2.y) + (p2.z + p2.w)) + ((p3.x + p3.y) + ((p3.z + p3.w) + fin)));
                    asm volatile("{\n.reg .pred p;\n.reg .b16 h;\nsetp.ne.u32 p, %2, 0;\ncvt.rn.bf16.f32 h, %1;\n@p st.global.b16 [%0], h;\n}"
                                 ::"l"(op), "f"(sum), "r"((uint32_t)(f == kF - 1 && threadIdx.x < kFW)) : "memory");
                }
                if (++slot == kNS) slot = 0;
            }
        }
    }
}

__global__ void __launch_bounds__(256)
attn_fallback(const __nv_bfloat16* __restrict__ q, const int* __restrict__ qk,
              const __nv_bfloat16* __restrict__ ksc, const __nv_bfloat16* __restrict__ kzp,
              const int* __restrict__ qv, const __nv_bfloat16* __restrict__ vsc,
              const __nv_bfloat16* __restrict__ vzp, const __nv_bfloat16* __restrict__ qcos,
              const __nv_bfloat16* __restrict__ qsin, const __nv_bfloat16* __restrict__ kcos,
              const __nv_bfloat16* __restrict__ ksin, __nv_bfloat16* __restrict__ out) {
    __shared__ float qr[kD], lg[kS], red[8];
    const int h = blockIdx.x, t = threadIdx.x, warp = t >> 5, lane = t & 31;
    if (t < kD) {
        const float x = __bfloat162float(q[h * kD + t]);
        const float y = t < kD / 2 ? -__bfloat162float(q[h * kD + t + kD / 2]) : __bfloat162float(q[h * kD + t - kD / 2]);
        qr[t] = bf_round(bf_round(x * __bfloat162float(qcos[t])) + bf_round(y * __bfloat162float(qsin[t])));
    }
    __syncthreads();
    const float scale_log2e = 1.4426950408889634f * rsqrtf((float)kD);
    float mw = -INFINITY;
    for (int s = warp; s < kS; s += 8) {
        const size_t row = (size_t)h * kS + s;
        const float z = __bfloat162float(kzp[row]);
        float dot = 0.f;
        for (int d = lane; d < kD; d += 32) {
            const int dp = d < kD / 2 ? d + kD / 2 : d - kD / 2;
            const float sn = __bfloat162float(ksin[s * kD + dp]);
            const float e = qr[d] * __bfloat162float(kcos[s * kD + d]) + qr[dp] * (d < kD / 2 ? sn : -sn);
            dot = fmaf((float)qk[row * kD + d] - z, e, dot);
        }
        for (int o = 16; o > 0; o >>= 1) dot += __shfl_xor_sync(0xffffffffu, dot, o);
        dot = dot * __bfloat162float(ksc[row]) * scale_log2e;
        if (lane == 0) lg[s] = dot;
        mw = fmaxf(mw, dot);
    }
    if (lane == 0) red[warp] = mw;
    __syncthreads();
    float M = red[0];
    for (int i = 1; i < 8; i++) M = fmaxf(M, red[i]);
    __syncthreads();
    float l = 0.f;
    for (int s = t; s < kS; s += 256) { const float p = exp2f(lg[s] - M); l += p; lg[s] = p; }
    for (int o = 16; o > 0; o >>= 1) l += __shfl_xor_sync(0xffffffffu, l, o);
    if (lane == 0) red[warp] = l;
    __syncthreads();
    float L = 0.f;
    for (int i = 0; i < 8; i++) L += red[i];
    if (t < kD) {
        float acc = 0.f;
        for (int s = 0; s < kS; s++) {
            const size_t row = (size_t)h * kS + s;
            acc = fmaf(lg[s] * __bfloat162float(vsc[row]), (float)qv[row * kD + t] - __bfloat162float(vzp[row]), acc);
        }
        out[h * kD + t] = __float2bfloat16_rn(acc / L);
    }
}

}

extern "C" void kernel_launch(void* const* d_in, const int* in_sizes, int n_in, void* d_out, int out_size) {
    const __nv_bfloat16* q = (const __nv_bfloat16*)d_in[0];
    const int* qk = (const int*)d_in[1];
    const __nv_bfloat16* ksc = (const __nv_bfloat16*)d_in[2];
    const __nv_bfloat16* kzp = (const __nv_bfloat16*)d_in[3];
    const int* qv = (const int*)d_in[4];
    const __nv_bfloat16* vsc = (const __nv_bfloat16*)d_in[5];
    const __nv_bfloat16* vzp = (const __nv_bfloat16*)d_in[6];
    const __nv_bfloat16* qcos = (const __nv_bfloat16*)d_in[7];
    const __nv_bfloat16* qsin = (const __nv_bfloat16*)d_in[8];
    const __nv_bfloat16* kcos = (const __nv_bfloat16*)d_in[9];
    const __nv_bfloat16* ksin = (const __nv_bfloat16*)d_in[10];

    typedef CUresult (*EncodeFn)(CUtensorMap*, CUtensorMapDataType, cuuint32_t, void*, const cuuint64_t*, const cuuint64_t*,
                                 const cuuint32_t*, const cuuint32_t*, CUtensorMapInterleave, CUtensorMapSwizzle,
                                 CUtensorMapL2promotion, CUtensorMapFloatOOBfill);
    static EncodeFn encode = nullptr;
    static int mode = 0;
    if (!mode) {
        int dev = 0, sms = 0, occ = 0;
        cudaGetDevice(&dev);
        cudaDeviceGetAttribute(&sms, cudaDevAttrMultiProcessorCount, dev);
        cudaError_t e = cudaFuncSetAttribute(attn_kernel, cudaFuncAttributeMaxDynamicSharedMemorySize, kSmemBytes);
        if (e == cudaSuccess) e = cudaOccupancyMaxActiveBlocksPerMultiprocessor(&occ, attn_kernel, kThreads, kSmemBytes);
        void* fn = nullptr;
        cudaDriverEntryPointQueryResult qr;
        if (e == cudaSuccess) e = cudaGetDriverEntryPoint("cuTensorMapEncodeTiled", &fn, cudaEnableDefault, &qr);
        encode = (EncodeFn)fn;
        mode = (e == cudaSuccess && fn && occ * sms >= kGrid) ? 1 : 2;
        (void)cudaGetLastError();
    }
    CUtensorMap tmv;
    bool fast = mode == 1;
    if (fast) {
        const cuuint64_t dims[2] = {(cuuint64_t)kD, (cuuint64_t)kNH * kS}, strides[1] = {(cuuint64_t)kRowBytes};
        const cuuint32_t box[2] = {(cuuint32_t)kFW, (cuuint32_t)(kFRows / kFBoxes)}, es[2] = {1, 1};
        fast = encode(&tmv, CU_TENSOR_MAP_DATA_TYPE_INT32, 2, (void*)qv, dims, strides, box, es, CU_TENSOR_MAP_INTERLEAVE_NONE,
                      CU_TENSOR_MAP_SWIZZLE_NONE, CU_TENSOR_MAP_L2_PROMOTION_L2_128B, CU_TENSOR_MAP_FLOAT_OOB_FILL_NONE) == CUDA_SUCCESS;
    }
    if (fast)
        attn_kernel<<<kGrid, kThreads, kSmemBytes>>>(Scalars{{ksc, kzp, vsc, vzp}}, qk, kcos, ksin, qv, q, qcos, qsin,
                                                     (__nv_bfloat16*)d_out, tmv);
    else
        attn_fallback<<<kNH, 256>>>(q, qk, ksc, kzp, qv, vsc, vzp, qcos, qsin, kcos, ksin, (__nv_bfloat16*)d_out);
}
```

```cpp
#include <cuda_runtime.h>
#include <cuda.h>
#include <cuda_bf16.h>
#include <stdint.h>

namespace {

constexpr int kB = 8, kH = 32, kS = 2048, kD = 192;
constexpr int kNH = kB * kH;
constexpr int kTeams = 4;
constexpr int kSlots = 32;
constexpr int kRows = kS / kSlots;
constexpr int kRounds = kNH / kTeams;
constexpr int kStream = kTeams * kSlots;
constexpr int kGrid = kStream + kTeams;
constexpr int kCW = 16;
constexpr int kR = kRows / kCW;
constexpr int kThreads = (kCW + 2) * 32;
constexpr int kRowBytes = kD * 4;
constexpr int kChunk = kRows * kRowBytes;
constexpr int kNS = 3;
constexpr int kHalf = kChunk / 2;
constexpr int kHRows = kRows / 2;
constexpr int kLead = 360;
constexpr int kLeadDef = 430;
constexpr int kRampEnd = 12, kRampStep = 70;
constexpr int kQuick = 20;
constexpr int kSleep = 200;
constexpr int kPR = 12;
constexpr int kScStride = 196;
constexpr int kOffScal = kNS * kChunk;
constexpr int kOffQ = kOffScal + kRounds * 4 * kRows * 2;
constexpr int kOffSc = kOffQ + kRounds * kD * 2;
constexpr int kOffBar = kOffSc + 2 * kCW * kScStride * 4;
constexpr int kF = 3;
constexpr int kFG = 4;
constexpr int kFW = kD / kFG;
constexpr int kFRows = kRows * kFG;
constexpr int kFHeads = kSlots / kFG;
constexpr int kDef0 = 16;
constexpr int kEarly = 4;
constexpr int kFBoxes = 16;
constexpr int kPrep = 40;
constexpr int kOffW = kOffScal;
constexpr int kOffFin = kOffW + kF * kFRows * 4;
constexpr int kPartStride = 20;
constexpr int kOffPart = kOffFin + kFW * 4;
constexpr int kOffMisc = kOffBar + (4 * kNS + 6 + kF * kFBoxes) * 8;
constexpr int kOffMax = kOffMisc + 16;
constexpr int kSmemBytes = kOffMax + 4 * kCW * 4;
constexpr int kRecWords = 112;
constexpr int kMG = 6;
static_assert(kNS >= 3, "ring");
static_assert(kOffBar % 8 == 0 && kOffSc % 16 == 0 && kOffMax % 16 == 0, "alignment");
static_assert(kPR % kMG == 0, "ring");
static_assert(kLead >= kStream && kS == kFHeads * kFRows && kFHeads == 8, "schedule");
static_assert(kSmemBytes <= 232448, "smem");
static_assert(kDef0 + kFHeads < kPrep && kPrep + 16 + 3 < kRounds && kEarly + kF * kFBoxes + 3 < kRounds && kOffPart <= kOffScal + (kPrep - 2) * 4 * kRows * 2 &&
              kOffPart + kF * kFW * kPartStride * 4 <= kOffScal + (kRounds - 2) * 4 * kRows * 2 && kF <= kNS && kFBoxes == kCW, "deferred rounds");

__device__ __align__(128) unsigned long long g_rec[kPR * kStream * kRecWords];
__device__ __align__(128) unsigned long long g_pre[kTeams * kFHeads * kRecWords];
__device__ __align__(128) unsigned long long g_lg[kTeams * kFHeads * kF * kFRows];
__device__ __align__(128) unsigned int g_prog;
__device__ __align__(128) unsigned int g_epoch;
__device__ __align__(128) unsigned int g_arrive;
__device__ __align__(128) unsigned int g_mdone[kTeams * kMG * 32];

constexpr int kSpin = 1 << 24;

__device__ __forceinline__ uint32_t s2u(const void* p) { return (uint32_t)__cvta_generic_to_shared(p); }
__device__ __forceinline__ void mbar_init(uint32_t a, int c) {
    asm volatile("mbarrier.init.shared::cta.b64 [%0], %1;" ::"r"(a), "r"(c));
}
__device__ __forceinline__ void mbar_wait(uint32_t a, uint32_t ph) {
    uint32_t ok;
    for (int it = 0;; it++) {
        asm volatile(
            "{\n.reg .pred p;\nmbarrier.try_wait.parity.shared::cta.b64 p, [%1], %2;\nselp.u32 %0, 1, 0, p;\n}"
            : "=r"(ok) : "r"(a), "r"(ph) : "memory");
        if (ok) break;
        if (it > kSpin) __trap();
    }
}
__device__ __forceinline__ void mbar_arrive(uint32_t a) {
    asm volatile("mbarrier.arrive.shared::cta.b64 _, [%0];" ::"r"(a) : "memory");
}
__device__ __forceinline__ void mbar_expect(uint32_t a, uint32_t bytes) {
    asm volatile("mbarrier.arrive.expect_tx.shared::cta.b64 _, [%0], %1;" ::"r"(a), "r"(bytes) : "memory");
}
__device__ __forceinline__ void bulk_g2s_stream(uint32_t dst, const void* src, uint32_t bytes, uint32_t mbar, uint64_t pol) {
    asm volatile("cp.async.bulk.shared::cluster.global.mbarrier::complete_tx::bytes.L2::cache_hint [%0], [%1], %2, [%3], %4;"
                 ::"r"(dst), "l"(src), "r"(bytes), "r"(mbar), "l"(pol) : "memory");
}
__device__ __forceinline__ void bulk_g2s(uint32_t dst, const void* src, uint32_t bytes, uint32_t mbar) {
    asm volatile("cp.async.bulk.shared::cluster.global.mbarrier::complete_tx::bytes [%0], [%1], %2, [%3];"
                 ::"r"(dst), "l"(src), "r"(bytes), "r"(mbar) : "memory");
}
__device__ __forceinline__ void cp16(uint32_t dst, const void* src) {
    asm volatile("cp.async.cg.shared.global [%0], [%1], 16;" ::"r"(dst), "l"(src) : "memory");
}
__device__ __forceinline__ float bf_lo(uint32_t u) { return __uint_as_float(u << 16); }
__device__ __forceinline__ float bf_hi(uint32_t u) { return __uint_as_float(u & 0xffff0000u); }
__device__ __forceinline__ float bf_round(float x) { return __bfloat162float(__float2bfloat16_rn(x)); }
__device__ __forceinline__ uint32_t ld_pair(const __nv_bfloat16* p) {
    return __ldg(reinterpret_cast<const uint32_t*>(p));
}
__device__ __forceinline__ unsigned int ld_relaxed(const unsigned int* p) {
    unsigned int v;
    asm volatile("ld.relaxed.gpu.global.u32 %0, [%1];" : "=r"(v) : "l"(p) : "memory");
    return v;
}
__device__ __forceinline__ unsigned long long pack_rec(float a, float b, uint32_t tag) {
    const uint32_t x = (__float_as_uint(a) & ~15u) | (tag & 15u), y = (__float_as_uint(b) & ~15u) | (tag >> 4);
    return ((unsigned long long)y << 32) | x;
}
__device__ __forceinline__ void st_rec(unsigned long long* p, float a, float b, uint32_t tag) {
    asm volatile("st.relaxed.gpu.global.b64 [%0], %1;" ::"l"(p), "l"(pack_rec(a, b, tag)) : "memory");
}
__device__ __forceinline__ float rec_lo(unsigned long long w) { return __uint_as_float((uint32_t)w & ~15u); }
__device__ __forceinline__ float rec_hi(unsigned long long w) { return __uint_as_float((uint32_t)(w >> 32) & ~15u); }
__device__ __forceinline__ unsigned long long ld_rec1(const unsigned long long* p) {
    unsigned long long x;
    asm volatile("ld.relaxed.gpu.global.b64 %0, [%1];" : "=l"(x) : "l"(p) : "memory");
    return x;
}
__device__ __forceinline__ void ld_rec2(const unsigned long long* p, unsigned long long& x, unsigned long long& y) {
    asm volatile("ld.relaxed.gpu.global.v2.b64 {%0, %1}, [%2];" : "=l"(x), "=l"(y) : "l"(p) : "memory");
}
__device__ __forceinline__ uint32_t rec_bad(unsigned long long w, uint32_t tlo, uint32_t thi) {
    return (((uint32_t)w ^ tlo) | ((uint32_t)(w >> 32) ^ thi)) & 15u;
}
__device__ __forceinline__ void st_ml(unsigned long long* p, float m, float l, uint32_t tag) {
    const uint32_t y = ((__float_as_uint(l) + 0x80u) & ~0xffu) | tag;
    asm volatile("st.relaxed.gpu.global.b64 [%0], %1;" ::"l"(p), "l"(((unsigned long long)y << 32) | __float_as_uint(m)) : "memory");
}
__device__ __forceinline__ uint32_t ml_bad(unsigned long long w, uint32_t tag) { return ((uint32_t)(w >> 32) ^ tag) & 0xffu; }
__device__ __forceinline__ float ml_m(unsigned long long w) { return __uint_as_float((uint32_t)w); }
__device__ __forceinline__ float ml_l(unsigned long long w) { return __uint_as_float((uint32_t)(w >> 32) & ~0xffu); }
__device__ __forceinline__ float warp_max(float v) {
    const int b = __float_as_int(v);
    const int k = __reduce_max_sync(0xffffffffu, b ^ ((b >> 31) & 0x7fffffff));
    return __int_as_float(k ^ ((k >> 31) & 0x7fffffff));
}
__device__ __forceinline__ uint32_t round_tag(unsigned int epoch, int r) {
    constexpr unsigned kUses = (kRounds + kPR - 1) / kPR;
    return (epoch * kUses + (unsigned)(r / kPR)) % 255u + 1u;
}

__device__ __forceinline__ void rotate_q(uint32_t* qrow, int p, uint32_t c_lo, uint32_t c_hi, uint32_t s_lo, uint32_t s_hi) {
    const uint32_t lo = qrow[p], hi = qrow[p + 48];
    const float a0 = bf_round(bf_lo(lo) * bf_lo(c_lo)) + bf_round(-bf_lo(hi) * bf_lo(s_lo));
    const float a1 = bf_round(bf_hi(lo) * bf_hi(c_lo)) + bf_round(-bf_hi(hi) * bf_hi(s_lo));
    const float b0 = bf_round(bf_lo(hi) * bf_lo(c_hi)) + bf_round(bf_lo(lo) * bf_lo(s_hi));
    const float b1 = bf_round(bf_hi(hi) * bf_hi(c_hi)) + bf_round(bf_hi(lo) * bf_hi(s_hi));
    const __nv_bfloat162 ua = __floats2bfloat162_rn(a0, a1), ub = __floats2bfloat162_rn(b0, b1);
    qrow[p] = *reinterpret_cast<const uint32_t*>(&ua);
    qrow[p + 48] = *reinterpret_cast<const uint32_t*>(&ub);
}
__device__ __forceinline__ int deferred_to(int blk, int r) {
    return (unsigned)(r - kDef0) < (unsigned)kFHeads ? (blk - kF * (r - kDef0)) & (kFHeads - 1) : kF;
}

__device__ __forceinline__ unsigned role_of_sm(unsigned smid) {
    const unsigned u = smid >> 1;
    const unsigned g = u < 32 ? u & 7 : u < 60 ? 1 + (u - 32) % 7 : u < 62 ? u - 54 : 0;
    const unsigned t = u < 32 ? u >> 3 : u < 60 ? 4 + (u - 32) / 7 : u < 62 ? 8 : u - 58;
    const unsigned lin = 16 * g + (g == 7 ? 2 : 0) + 2 * t + (smid & 1);
    return lin < 48 ? lin : lin < 52 ? lin + (kStream - 48) : lin - 4;
}
static_assert(kGrid == 132 && kTeams == 4, "role_of_sm");
struct Scalars { const __nv_bfloat16* p[4]; };

__global__ void __launch_bounds__(kThreads, 1)
attn_kernel(const __grid_constant__ Scalars scal, const int* __restrict__ qk, int by_sm, const __nv_bfloat16* __restrict__ kcos,
            const __nv_bfloat16* __restrict__ ksin, const int* __restrict__ qv, const __nv_bfloat16* __restrict__ q,
            const __nv_bfloat16* __restrict__ qcos, const __nv_bfloat16* __restrict__ qsin,
            __nv_bfloat16* __restrict__ out, const __grid_constant__ CUtensorMap tmv) {
    extern __shared__ __align__(128) unsigned char smem[];
    const int warp = threadIdx.x >> 5, lane = threadIdx.x & 31;
    const uint32_t full0 = s2u(smem + kOffBar), empty0 = full0 + 2 * kNS * 8;
    const uint32_t sfull = empty0 + 2 * kNS * 8, sempty = sfull + 16, mxbar = sempty + 16, fine = mxbar + 16;
    volatile unsigned int* s_misc = reinterpret_cast<volatile unsigned int*>(smem + kOffMisc);
    uint64_t pol = 0;

    if (threadIdx.x == kCW * 32 && blockIdx.x < kStream)
        asm volatile("cp.async.bulk.prefetch.L2.global [%0], %1;"
                     ::"l"(scal.p[blockIdx.x & 3] + (blockIdx.x >> 2) * (kNH * kS * 4 / kStream)), "n"(kNH * kS * 4 / kStream * 2) : "memory");
    unsigned bid = blockIdx.x;
    if (by_sm) {
        unsigned smid, nsm;
        asm volatile("mov.u32 %0, %%smid;" : "=r"(smid));
        asm volatile("mov.u32 %0, %%nsmid;" : "=r"(nsm));
        if (nsm == kGrid) bid = role_of_sm(smid);
    }
    if (threadIdx.x == kCW * 32 && bid < kStream) {
        const int m = bid % kSlots;
        const uint32_t sm0 = s2u(smem);
        for (int i = 0; i < 2 * kNS; i++) mbar_init(full0 + 8 * i, 1);
        asm volatile("fence.mbarrier_init.release.cluster;" ::: "memory");
        asm volatile("createpolicy.fractional.L2::evict_first.b64 %0, 1.0;" : "=l"(pol));
        const int* k0 = qk + (size_t)(bid / kSlots * kS + m * kHRows) * kD;
#pragma unroll
        for (int h = 0; h < 2; h++) {
            mbar_expect(full0 + 16 + 8 * h, kHalf);
            bulk_g2s_stream(sm0 + kChunk + h * kHalf, k0 + h * (kS / 2 * kD), kHalf, full0 + 16 + 8 * h, pol);
        }
#pragma unroll
        for (int h = 0; h < 2; h++) {
            mbar_expect(full0 + 8 * h, kHalf);
            bulk_g2s(sm0 + h * kHalf, kcos + (h * (kS / 2) + m * kHRows) * kD, kHalf / 2, full0 + 8 * h);
            bulk_g2s(sm0 + h * kHalf + kHalf / 2, ksin + (h * (kS / 2) + m * kHRows) * kD, kHalf / 2, full0 + 8 * h);
        }
#pragma unroll
        for (int h = 0; h < 2; h++) {
            mbar_expect(full0 + 32 + 8 * h, kHalf);
            bulk_g2s_stream(sm0 + 2 * kChunk + h * kHalf, k0 + (kTeams * kS + h * (kS / 2)) * kD, kHalf, full0 + 32 + 8 * h, pol);
        }
    }

    if (bid >= kStream) {
        const int team = bid - kStream;
        if (threadIdx.x == 0) s_misc[0] = ld_relaxed(&g_epoch);
        __syncthreads();
        if (threadIdx.x == 0 && atomicAdd(&g_arrive, 1u) == kGrid - 1) { g_arrive = 0u; g_epoch = s_misc[0] + 1u; }
        if (warp >= 3 * kMG) return;
        const int grp = warp / 3, t = threadIdx.x - grp * 96;
        constexpr int kRecBytes = kSlots * kRecWords * 8;
        if (t == 0) {
            mbar_init(s2u(smem + kOffBar) + grp * 8, 1);
            asm volatile("fence.mbarrier_init.release.cluster;" ::: "memory");
        }
        asm volatile("bar.sync %0, 96;" ::"r"(3 + grp) : "memory");
        for (int r = grp; r < kRounds; r += kMG) {
            const int g = r % kMG;
            const int tt = threadIdx.x - g * 96, qd = tt % 48, half = tt / 48;
            const uint32_t tag = round_tag(s_misc[0], r);
            const uint32_t tlo = tag & 15u, thi = tag >> 4;
            const unsigned long long* rec = g_rec + ((size_t)(r % kPR) * kStream + team * kSlots) * kRecWords;
            unsigned long long ml, x[16], y[16];
            {
                const unsigned long long* buf = reinterpret_cast<const unsigned long long*>(smem + g * kRecBytes);
                const uint32_t mb = s2u(smem + kOffBar) + g * 8;
                if (tt < 32) {
                    const int want = r == kRounds - 1 ? kQuick : kSlots;
                    for (int i2 = 0;; i2++) {
                        ml = ld_rec1(rec + lane * kRecWords + 96);
                        if (__popc(__ballot_sync(0xffffffffu, ml_bad(ml, tag) == 0)) >= want) break;
                        if (i2 > kSpin) __trap();
                        __nanosleep(kSleep);
                    }
                    if (tt == 0) {
                        mbar_expect(mb, kRecBytes);
                        bulk_g2s(s2u(buf), rec, kRecBytes, mb);
                    }
                }
                mbar_wait(mb, (r / kMG) & 1);
                ml = buf[lane * kRecWords + 96];
#pragma unroll
                for (int i = 0; i < 16; i++) {
                    const ulonglong2 u = *reinterpret_cast<const ulonglong2*>(buf + (half * 16 + i) * kRecWords + 2 * qd);
                    x[i] = u.x; y[i] = u.y;
                }
                const unsigned long long* po = rec + half * 16 * kRecWords + 2 * qd;
                for (int it = 0;; it++) {
                    uint32_t any = ml_bad(ml, tag);
                    if (any) ml = ld_rec1(rec + lane * kRecWords + 96);
#pragma unroll
                    for (int i = 0; i < 16; i++) {
                        const uint32_t bad = rec_bad(x[i], tlo, thi) | rec_bad(y[i], tlo, thi);
                        if (bad) ld_rec2(po + i * kRecWords, x[i], y[i]);
                        any |= bad;
                    }
                    if (__all_sync(0xffffffffu, any == 0)) break;
                    if (it > kSpin) __trap();
                }
            }
            const float M = ml_m(ml);
            const float MM = warp_max(M);
            const float w = exp2f(M - MM);
            float LL = w * ml_l(ml);
#pragma unroll
            for (int o = 16; o > 0; o >>= 1) LL += __shfl_xor_sync(0xffffffffu, LL, o);
            float4 a = make_float4(0.f, 0.f, 0.f, 0.f);
#pragma unroll
            for (int i = 0; i < 16; i++) {
                const float wi = __shfl_sync(0xffffffffu, w, half * 16 + i);
                a.x = fmaf(wi, rec_lo(x[i]), a.x);
                a.y = fmaf(wi, rec_hi(x[i]), a.y);
                a.z = fmaf(wi, rec_lo(y[i]), a.z);
                a.w = fmaf(wi, rec_hi(y[i]), a.w);
            }
            float* rb = reinterpret_cast<float*>(smem + kMG * kRecBytes) + (2 * g + ((r / kMG) & 1)) * kD + 4 * qd;
            if (half == 1) *reinterpret_cast<float4*>(rb) = a;
            asm volatile("bar.sync %0, 96;" ::"r"(3 + g) : "memory");
            if (half == 0) {
                const float4 u = *reinterpret_cast<float4*>(rb);
                if ((unsigned)(r - kDef0) < (unsigned)kFHeads) {
                    unsigned long long* pre = g_pre + (size_t)(team * kFHeads + r - kDef0) * kRecWords;
                    const uint32_t ptag = s_misc[0] % 255u + 1u;
                    st_rec(pre + 2 * qd, a.x + u.x, a.y + u.y, ptag);
                    st_rec(pre + 2 * qd + 1, a.z + u.z, a.w + u.w, ptag);
                    if (qd == 0) st_ml(pre + 96, MM, LL, ptag);
                } else {
                    const float inv = __fdividef(1.0f, LL);
                    const __nv_bfloat162 o0 = __floats2bfloat162_rn((a.x + u.x) * inv, (a.y + u.y) * inv);
                    const __nv_bfloat162 o1 = __floats2bfloat162_rn((a.z + u.z) * inv, (a.w + u.w) * inv);
                    uint2 ov;
                    ov.x = *reinterpret_cast<const uint32_t*>(&o0);
                    ov.y = *reinterpret_cast<const uint32_t*>(&o1);
                    *reinterpret_cast<uint2*>(out + (size_t)(kTeams * r + team) * kD + 4 * qd) = ov;
                }
            }
            if (tt == 95)
                asm volatile("st.relaxed.gpu.global.u32 [%0], %1;" ::"l"(&g_mdone[(team * kMG + g) * 32]), "r"(s_misc[0] * kRounds + r + 1) : "memory");
        }
        return;
    }

    const int m = bid % kSlots, team = bid / kSlots;
    const int row0 = m * kHRows;

    if (warp == kCW) {
        unsigned int epoch = 0;
        const size_t off0 = ((size_t)team * kS + row0) * kD;
        const uint32_t sm0 = s2u(smem);
        if (lane == 0) {
            epoch = ld_relaxed(&g_epoch);
            s_misc[0] = epoch;
        }
        __syncwarp();
        asm volatile("bar.sync 2, %0;" ::"n"(kThreads) : "memory");
        if (lane == 0) {
            unsigned int cum = epoch * (kStream * (4 * kRounds - 2)) + 4 * kStream;
            unsigned int seen = cum - 4 * kStream;
            unsigned int need = seen;
            int use0 = kNS, use1 = kNS;
            const unsigned int* prog = &g_prog;
            const int* kp = qk + off0;
            const int* vp = qv + off0;
            for (int ph2 = 4; ph2 < 2 * (2 * kRounds + kF); ph2++) {
                unsigned int v = seen;
                asm volatile("{\n.reg .pred p;\nsetp.lt.s32 p, %2, 0;\n@p ld.relaxed.gpu.global.u32 %0, [%1];\n}"
                             : "+r"(v) : "l"(prog), "r"(seen - need) : "memory");
                const int p = ph2 >> 1, h = ph2 & 1;
                const bool isv = (p & 1) == 0 || p == 2 * kRounds - 1;
                const int r = p == 2 * kRounds - 1 ? kRounds - 1 : isv ? (p >> 1) - 1 : (p + 1) >> 1;
                const uint32_t dm = (isv && (unsigned)(r - kDef0) < (unsigned)kFHeads)
                                        ? ((((1u << kF) - 1) * 0x101u << ((kF * (r - kDef0)) & (kFHeads - 1))) >> (8 + 4 * h)) & 15u : 0u;
                cum += kStream - (kStream / 4) * __popc(dm);
                const unsigned int need_next = cum - max(kRampEnd - (ph2 + 1), 0) * kRampStep -
                    ((unsigned)(ph2 + 1 - (4 * kDef0 + 4)) < (unsigned)(4 * kFHeads + 2) ? kLeadDef : kLead);
                const bool skip = (dm >> (m / 8)) & 1;
                const int u = h ? use1 : use0;
                const int slot = u >= kNS ? u - kNS : u;
                const uint32_t dst = sm0 + slot * kChunk + h * kHalf, fullb = full0 + 16 * slot + 8 * h;
                const int* src = (isv ? vp : kp) + (size_t)(r * kTeams * kS + h * (kS / 2)) * kD;
                if (!skip) {
                    const int un = u + 1 == 2 * kNS ? 0 : u + 1;
                    if (h) use1 = un; else use0 = un;
                    mbar_wait(fullb + 2 * kNS * 8, u >= kNS ? 0 : 1);
                    if (p < 2 * kRounds) mbar_expect(fullb, kHalf);
                }
                asm volatile("" ::"r"(need_next), "l"(src), "r"(dst) : "memory");
                seen = v;
                if (!skip)
                    for (int it = 0; (int)(seen - need) < 0; it++) {
                        seen = ld_relaxed(prog);
                        if (it > kSpin) __trap();
                    }
                need = need_next;
                if (p >= 2 * kRounds || skip) {
                    const int hi = m / kFG;
                    const int row = (kTeams * (kDef0 + hi) + team) * kS + ((kF * hi + p - 2 * kRounds) & (kFHeads - 1)) * kFRows + h * (kFRows / 2);
                    const uint32_t fb = fine + 8 * (kFBoxes / 2) * (ph2 - 4 * kRounds);
#pragma unroll 1
                    for (int w = 0; w < kFBoxes / 2; w++)
                        asm volatile("{\n.reg .pred p;\nsetp.ne.u32 p, %6, 0;\n"
                                     "@p cp.async.bulk.tensor.2d.shared::cluster.global.tile.mbarrier::complete_tx::bytes.L2::cache_hint [%0], [%1, {%2, %3}], [%4], %5;\n}"
                                     ::"r"(dst + w * (kChunk / kFBoxes)), "l"(&tmv), "r"((m % kFG) * kFW), "r"(row + w * (kFRows / kFBoxes)),
                                       "r"(fb + 8 * w), "l"(pol), "r"((uint32_t)!skip) : "memory");
                } else {
                    bulk_g2s_stream(dst, src, kHalf, fullb, pol);
                }
            }
        }
    } else if (warp == kCW + 1) {
        {
            if (lane < 2 * kNS + 6) mbar_init(empty0 + 8 * lane, lane < 2 * kNS ? kCW / 2 : (lane >= 2 * kNS + 2 && lane < 2 * kNS + 4) ? 1 : kCW);
            asm volatile("fence.mbarrier_init.release.cluster;" ::: "memory");
        }
        asm volatile("bar.sync 2, %0;" ::"n"(kThreads) : "memory");
        const unsigned int epoch = s_misc[0];
        if (lane == 0 && atomicAdd(&g_arrive, 1u) == kGrid - 1) { g_arrive = 0u; g_epoch = epoch + 1u; }
        {
            const uint32_t sm0 = s2u(smem);
            const __nv_bfloat16* src = scal.p[lane >> 3] + (size_t)team * kS + row0 + (lane & 4) * (kS / 8) + (lane & 3) * 8;
            const __nv_bfloat16* qs = q + team * kD + lane * 8;
#pragma unroll 1
            for (int r = kEarly; r < kRounds; r++) {
                cp16(sm0 + kOffScal + r * 512 + lane * 16, src + (size_t)r * (kTeams * kS));
                if (lane < 24) cp16(sm0 + kOffQ + r * (kD * 2) + lane * 16, qs + r * (kTeams * kD));
                if (r == 2 * kEarly - 1 || r == kRounds - 1) asm volatile("cp.async.commit_group;" ::: "memory");
            }
        }
        uint32_t cs[2][4];
#pragma unroll
        for (int i = 0; i < 2; i++) {
            const int p = (lane + 32 * i) % 48;
            cs[i][0] = ld_pair(qcos + 2 * p); cs[i][1] = ld_pair(qcos + 2 * p + 96);
            cs[i][2] = ld_pair(qsin + 2 * p); cs[i][3] = ld_pair(qsin + 2 * p + 96);
        }
        asm volatile("cp.async.wait_group 1;" ::: "memory");
        __syncwarp();
        for (int r = 0; r < kRounds; r++) {
            const float* sc = reinterpret_cast<const float*>(smem + kOffSc) + (r & 1) * (kCW * kScStride);
            const uint32_t tag = round_tag(epoch, r);
            unsigned long long* rec = g_rec + ((size_t)(r % kPR) * kStream + team * kSlots + m) * kRecWords;
            if (r >= kEarly && r < kEarly + kF * kFBoxes && lane == 0) {
                mbar_init(fine + 8 * (r - kEarly), 1);
                asm volatile("fence.mbarrier_init.release.cluster;" ::: "memory");
                mbar_expect(fine + 8 * (r - kEarly), kChunk / kFBoxes);
                asm volatile("fence.proxy.async.shared::cta;" ::: "memory");
            }
            if (r == kPrep + m / 2) {
                const unsigned long long* pre = g_pre + (size_t)(team * kFHeads + m / kFG) * kRecWords;
                const unsigned long long* lgp = g_lg + (size_t)(team * kFHeads + m / kFG) * (kF * kFRows);
                const uint32_t ptag = epoch % 255u + 1u;
                unsigned long long ml, po;
                for (int it = 0;; it++) {
                    ml = ld_rec1(pre + 96);
                    po = ld_rec1(pre + (m % kFG) * (kFW / 2) + lane % (kFW / 2));
                    if (!(ml_bad(ml, ptag) | rec_bad(po, ptag & 15u, ptag >> 4))) break;
                    if (it > kSpin) __trap();
                }
                const float inv = 1.0f / ml_l(ml);
                if (lane < kFW / 2) {
                    reinterpret_cast<float*>(smem + kOffFin)[lane] = rec_lo(po) * inv;
                    reinterpret_cast<float*>(smem + kOffFin)[kFW / 2 + lane] = rec_hi(po) * inv;
                }
#pragma unroll 1
                for (int c = 0; c < kF; c++) {
                    unsigned long long u[8];
                    for (int it = 0;; it++) {
                        uint32_t bad = 0;
#pragma unroll
                        for (int k = 0; k < 8; k++) {
                            u[k] = ld_rec1(lgp + c * kFRows + 32 * k + lane);
                            bad |= ml_bad(u[k], ptag);
                        }
                        if (!bad) break;
                        if (it > kSpin) __trap();
                    }
#pragma unroll
                    for (int k = 0; k < 8; k++)
                        reinterpret_cast<float*>(smem + kOffW)[c * kFRows + 32 * k + lane] = ml_l(u[k]) * exp2f(ml_m(u[k]) - ml_m(ml)) * inv;
                }
                __syncwarp();
            }
            if (r == kRounds - 3 && lane == 0) asm volatile("prefetch.tensormap [%0];" ::"l"(&tmv) : "memory");
            if (r == kEarly) {
                asm volatile("cp.async.wait_all;" ::: "memory");
                __syncwarp();
            }
            if (r + kEarly < kRounds) {
                uint32_t* qrow = reinterpret_cast<uint32_t*>(smem + kOffQ + (r + kEarly) * (kD * 2));
                rotate_q(qrow, lane, cs[0][0], cs[0][1], cs[0][2], cs[0][3]);
                if (lane < 16) rotate_q(qrow, lane + 32, cs[1][0], cs[1][1], cs[1][2], cs[1][3]);
            }
            if (r >= kPR) {
                const unsigned int* mdone = &g_mdone[(team * kMG + r % kMG) * 32];
                const unsigned int need = epoch * kRounds + r - kPR + 1;
                for (int it = 0; (int)(ld_relaxed(mdone) - need) < 0; it++)
                    if (it > kSpin) __trap();
            }
            mbar_wait(sfull + 8 * (r & 1), (r >> 1) & 1);
            const float M = sc[0];
            float L = lane < kCW ? sc[lane * kScStride + 1] : 0.f;
            float acc[2][6];
#pragma unroll
            for (int ww = 0; ww < kCW; ww++) {
#pragma unroll
                for (int j = 0; j < 3; j++) {
                    const float2 t = *reinterpret_cast<const float2*>(sc + ww * kScStride + 4 + 64 * j + 2 * lane);
                    acc[ww & 1][2 * j] = ww < 2 ? t.x : acc[ww & 1][2 * j] + t.x;
                    acc[ww & 1][2 * j + 1] = ww < 2 ? t.y : acc[ww & 1][2 * j + 1] + t.y;
                }
                if ((ww & 3) == 3 && ww < 15) L += __shfl_xor_sync(0xffffffffu, L, 8 >> (ww >> 2));
            }
            L += __shfl_xor_sync(0xffffffffu, L, 1);
#pragma unroll
            for (int j = 0; j < 3; j++)
                st_rec(rec + 32 * j + lane, acc[0][2 * j] + acc[1][2 * j], acc[0][2 * j + 1] + acc[1][2 * j + 1], tag);
            if (lane == 0) st_ml(rec + 96, M, L, tag);
            __syncwarp();
            if (lane == 0) mbar_arrive(sempty + 8 * (r & 1));
        }
    } else {
        int dp[3];
#pragma unroll
        for (int j = 0; j < 3; j++) dp[j] = (64 * j + 2 * lane + 96) % kD;
        {
            const uint32_t sm0 = s2u(smem);
            if (warp < kEarly) {
                cp16(sm0 + kOffScal + threadIdx.x * 16, scal.p[lane >> 3] + (size_t)(kTeams * warp + team) * kS + row0 + (lane & 4) * (kS / 8) + (lane & 3) * 8);
            } else if (warp < 2 * kEarly && lane < 24) {
                cp16(sm0 + kOffQ + (warp - kEarly) * (kD * 2) + lane * 16, q + (size_t)(kTeams * (warp - kEarly) + team) * kD + lane * 8);
            }
            asm volatile("cp.async.commit_group;" ::: "memory");
        }
        const int p = threadIdx.x % 48, g = threadIdx.x / 48;
        const uint32_t c_lo = ld_pair(qcos + 2 * p), c_hi = ld_pair(qcos + 2 * p + 96);
        const uint32_t s_lo = ld_pair(qsin + 2 * p), s_hi = ld_pair(qsin + 2 * p + 96);
        float kc[kR][6], ks[kR][6];
        asm volatile("bar.sync 2, %0;" ::"n"(kThreads) : "memory");
        const int half = warp / (kCW / 2);
        const uint32_t fullh = full0 + 8 * half, emptyh = empty0 + 8 * half;
        mbar_wait(fullh, 0);
#pragma unroll
        for (int i = 0; i < kR; i++) {
            const unsigned char* cb = smem + half * (kHalf / 2) + (warp * kR + i) * (kD * 2);
#pragma unroll
            for (int j = 0; j < 3; j++) {
                const uint32_t uc = *reinterpret_cast<const uint32_t*>(cb + 128 * j + 4 * lane);
                const uint32_t us = *reinterpret_cast<const uint32_t*>(cb + kHalf / 2 + 2 * dp[j]);
                kc[i][2 * j] = bf_lo(uc); kc[i][2 * j + 1] = bf_hi(uc);
                const float sg = (j == 0 || (j == 1 && lane < 16)) ? 1.f : -1.f;
                ks[i][2 * j] = sg * bf_lo(us); ks[i][2 * j + 1] = sg * bf_hi(us);
            }
        }
        __syncwarp();
        if (lane == 0) mbar_arrive(emptyh);
        asm volatile("cp.async.wait_group 0;" ::: "memory");
        asm volatile("bar.sync 1, %0;" ::"n"(kCW * 32) : "memory");
        if (g < kEarly) rotate_q(reinterpret_cast<uint32_t*>(smem + kOffQ + g * (kD * 2)), p, c_lo, c_hi, s_lo, s_hi);
        asm volatile("bar.sync 1, %0;" ::"n"(kCW * 32) : "memory");
        const float scale_log2e = 1.4426950408889634f * rsqrtf((float)kD);
        float* my0 = reinterpret_cast<float*>(smem + kOffSc) + warp * kScStride;

        float* s_max = reinterpret_cast<float*>(smem + kOffMax);
        int slot = 1;
        uint32_t ph = 0;
        float lgc[kR] = {0.f, 0.f, 0.f, 0.f};
        for (int it = 0; it <= kRounds; it++) {
            float lg[kR];
            if (it < kRounds) {
                float qa[6], qb[6];
#pragma unroll
                for (int j = 0; j < 3; j++) {
                    const uint32_t qo = *reinterpret_cast<const uint32_t*>(smem + kOffQ + it * (kD * 2) + 2 * (64 * j + 2 * lane));
                    const uint32_t qp = *reinterpret_cast<const uint32_t*>(smem + kOffQ + it * (kD * 2) + 2 * dp[j]);
                    qa[2 * j] = bf_lo(qo); qa[2 * j + 1] = bf_hi(qo);
                    qb[2 * j] = bf_lo(qp); qb[2 * j + 1] = bf_hi(qp);
                }
                const unsigned char* sp = smem + kOffScal + it * (4 * kRows * 2) + warp * (kR * 2);
                const uint2 uks = *reinterpret_cast<const uint2*>(sp);
                const uint2 ukz = *reinterpret_cast<const uint2*>(sp + kRows * 2);
                const float kz[4] = {bf_lo(ukz.x), bf_hi(ukz.x), bf_lo(ukz.y), bf_hi(ukz.y)};
                const float sk[4] = {bf_lo(uks.x), bf_hi(uks.x), bf_lo(uks.y), bf_hi(uks.y)};
                mbar_wait(fullh + 16 * slot, ph);
                if ((threadIdx.x & 255) == 0) asm volatile("red.relaxed.gpu.global.add.u32 [%0], 1;" ::"l"(&g_prog) : "memory");
                const unsigned char* kb = smem + slot * kChunk + warp * (kR * kRowBytes) + lane * 8;
#pragma unroll
                for (int i = 0; i < kR; i++) {
                    float dot = 0.f;
#pragma unroll
                    for (int j = 0; j < 3; j++) {
                        const int2 kk = *reinterpret_cast<const int2*>(kb + i * kRowBytes + 256 * j);
                        const float e0 = qa[2 * j] * kc[i][2 * j] + qb[2 * j] * ks[i][2 * j];
                        const float e1 = qa[2 * j + 1] * kc[i][2 * j + 1] + qb[2 * j + 1] * ks[i][2 * j + 1];
                        dot = fmaf((float)kk.x - kz[i], e0, dot);
                        dot = fmaf((float)kk.y - kz[i], e1, dot);
                    }
                    lg[i] = dot;
                }
                __syncwarp();
                if (lane == 0) mbar_arrive(emptyh + 16 * slot);
                if (++slot == kNS) { slot = 0; ph ^= 1; }
#pragma unroll
                for (int o = 16; o > 0; o >>= 1) {
#pragma unroll
                    for (int i = 0; i < kR; i++) lg[i] += __shfl_xor_sync(0xffffffffu, lg[i], o);
                }
                float mw = -INFINITY;
#pragma unroll
                for (int i = 0; i < kR; i++) {
                    lg[i] = lg[i] * sk[i] * scale_log2e;
                    mw = fmaxf(mw, lg[i]);
                }
                if (lane == 0) {
                    s_max[(it & 3) * kCW + warp] = mw;
                    mbar_arrive(mxbar + 8 * (it & 1));
                }
            }
            if (it > 0) {
                const int r = it - 1;
                float* my = my0 + (r & 1) * (kCW * kScStride);
                const int df = deferred_to(4 * half + m / 8, r);
                const unsigned char* sp = smem + kOffScal + r * (4 * kRows * 2) + warp * (kR * 2);
                const uint2 uvs = *reinterpret_cast<const uint2*>(sp + 2 * kRows * 2);
                const uint2 uvz = *reinterpret_cast<const uint2*>(sp + 3 * kRows * 2);
                const float vz[4] = {bf_lo(uvz.x), bf_hi(uvz.x), bf_lo(uvz.y), bf_hi(uvz.y)};
                const float sv[4] = {bf_lo(uvs.x), bf_hi(uvs.x), bf_lo(uvs.y), bf_hi(uvs.y)};
                mbar_wait(mxbar + 8 * (r & 1), (r >> 1) & 1);
                float M;
                {
                    const float4* pm4 = reinterpret_cast<const float4*>(s_max + (r & 3) * kCW);
                    const float4 m0 = pm4[0], m1 = pm4[1], m2 = pm4[2], m3 = pm4[3];
                    M = fmaxf(fmaxf(fmaxf(fmaxf(m0.x, m0.y), fmaxf(m0.z, m0.w)), fmaxf(fmaxf(m1.x, m1.y), fmaxf(m1.z, m1.w))),
                              fmaxf(fmaxf(fmaxf(m2.x, m2.y), fmaxf(m2.z, m2.w)), fmaxf(fmaxf(m3.x, m3.y), fmaxf(m3.z, m3.w))));
                }
                float lw = 0.f, cz = 0.f, pv[kR];
#pragma unroll
                for (int i = 0; i < kR; i++) {
                    const float p = exp2f(lgc[i] - M);
                    lw += p;
                    pv[i] = p * sv[i];
                    cz = fmaf(pv[i], vz[i], cz);
                }
                mbar_wait(sempty + 8 * (r & 1), ((r >> 1) & 1) ^ 1);
                if (lane == 0) { my[0] = M; my[1] = lw; }
                float acc[6] = {-cz, -cz, -cz, -cz, -cz, -cz};
                if (df < kF) {
                    if (lane < kR)
                        st_ml(g_lg + ((team * kFHeads + r - kDef0) * kF + df) * kFRows + (m % 8) * kHRows + (warp % 8) * kR + lane, M,
                              lane == 0 ? pv[0] : lane == 1 ? pv[1] : lane == 2 ? pv[2] : pv[3], s_misc[0] % 255u + 1u);
                } else {
                    mbar_wait(fullh + 16 * slot, ph);
                    if ((threadIdx.x & 255) == 0) asm volatile("red.relaxed.gpu.global.add.u32 [%0], 1;" ::"l"(&g_prog) : "memory");
                    const unsigned char* vb = smem + slot * kChunk + warp * (kR * kRowBytes) + lane * 8;
#pragma unroll
                    for (int i = 0; i < kR; i++) {
#pragma unroll
                        for (int j = 0; j < 3; j++) {
                            const int2 vv = *reinterpret_cast<const int2*>(vb + i * kRowBytes + 256 * j);
                            acc[2 * j] = fmaf(pv[i], (float)vv.x, acc[2 * j]);
                            acc[2 * j + 1] = fmaf(pv[i], (float)vv.y, acc[2 * j + 1]);
                        }
                    }
                    __syncwarp();
                    if (lane == 0) mbar_arrive(emptyh + 16 * slot);
                    if (++slot == kNS) { slot = 0; ph ^= 1; }
                }
#pragma unroll
                for (int j = 0; j < 3; j++)
                    *reinterpret_cast<float2*>(my + 4 + 64 * j + 2 * lane) = make_float2(acc[2 * j], acc[2 * j + 1]);
                __syncwarp();
                if (lane == 0) mbar_arrive(sfull + 8 * (r & 1));
            }
#pragma unroll
            for (int i = 0; i < kR; i++) lgc[i] = lg[i];
        }
        {
            const int cp = lane < kFW / 2 ? lane : 0;
            const int ft = threadIdx.x < kFW ? threadIdx.x : 0;
            const float fin = reinterpret_cast<const float*>(smem + kOffFin)[ft];
            __nv_bfloat16* op = out + (size_t)(kTeams * (kDef0 + m / kFG) + team) * kD + (m % kFG) * kFW + 2 * (ft % (kFW / 2)) + ft / (kFW / 2);
            float a0 = 0.f, a1 = 0.f, b0 = 0.f, b1 = 0.f;
#pragma unroll 1
            for (int f = 0; f < kF; f++) {
                const float* sw = reinterpret_cast<const float*>(smem + kOffW) + f * kFRows + (warp >> 2) * 16 + (warp & 3) * 4;
                const unsigned char* vb = smem + slot * kChunk + ((warp >> 2) * 16 + (warp & 3) * 4) * (kFW * 4) + cp * 8;
                const uint32_t fb = fine + (f * kFBoxes + (warp >> 2)) * 8;
                float* part = reinterpret_cast<float*>(smem + kOffPart) + f * (kFW * kPartStride);
                float4 w[4];
#pragma unroll
                for (int k = 0; k < 4; k++) w[k] = *reinterpret_cast<const float4*>(sw + 64 * k);
#pragma unroll
                for (int k = 0; k < 4; k++) {
                    mbar_wait(fb + 32 * k, 0);
                    if ((k & 1) && threadIdx.x == kCW * 32 - 32 && f < kF - 1) asm volatile("red.relaxed.gpu.global.add.u32 [%0], 1;" ::"l"(&g_prog) : "memory");
                    const int2 v0 = *reinterpret_cast<const int2*>(vb + k * (64 * kFW * 4));
                    const int2 v1 = *reinterpret_cast<const int2*>(vb + k * (64 * kFW * 4) + kFW * 4);
                    const int2 v2 = *reinterpret_cast<const int2*>(vb + k * (64 * kFW * 4) + 2 * kFW * 4);
                    const int2 v3 = *reinterpret_cast<const int2*>(vb + k * (64 * kFW * 4) + 3 * kFW * 4);
                    a0 = fmaf(w[k].x, (float)v0.x, a0); a1 = fmaf(w[k].x, (float)v0.y, a1);
                    b0 = fmaf(w[k].y, (float)v1.x, b0); b1 = fmaf(w[k].y, (float)v1.y, b1);
                    a0 = fmaf(w[k].z, (float)v2.x, a0); a1 = fmaf(w[k].z, (float)v2.y, a1);
                    b0 = fmaf(w[k].w, (float)v3.x, b0); b1 = fmaf(w[k].w, (float)v3.y, b1);
                }
                if (lane < kFW / 2) {
                    part[lane * kPartStride + warp] = a0 + b0;
                    part[(kFW / 2 + lane) * kPartStride + warp] = a1 + b1;
                }
                if (warp >= 2) {
                    asm volatile("bar.arrive %0, %1;" ::"r"(3 + f), "n"(kCW * 32) : "memory");
                } else {
                    asm volatile("bar.sync %0, %1;" ::"r"(3 + f), "n"(kCW * 32) : "memory");
                    const float4* ps = reinterpret_cast<const float4*>(part + ft * kPartStride);
                    const float4 p0 = ps[0], p1 = ps[1], p2 = ps[2], p3 = ps[3];
                    const float sum = (((p0.x + p0.y) + (p0.z + p0.w)) + ((p1.x + p1.y) + (p1.z + p1.w))) +
                                      (((p2.x + p2.y) + (p2.z + p2.w)) + ((p3.x + p3.y) + ((p3.z + p3.w) + fin)));
                    asm volatile("{\n.reg .pred p;\n.reg .b16 h;\nsetp.ne.u32 p, %2, 0;\ncvt.rn.bf16.f32 h, %1;\n@p st.global.b16 [%0], h;\n}"
                                 ::"l"(op), "f"(sum), "r"((uint32_t)(f == kF - 1 && threadIdx.x < kFW)) : "memory");
                }
                if (++slot == kNS) slot = 0;
            }
        }
    }
}

__global__ void __launch_bounds__(256)
attn_fallback(const __nv_bfloat16* __restrict__ q, const int* __restrict__ qk,
              const __nv_bfloat16* __restrict__ ksc, const __nv_bfloat16* __restrict__ kzp,
              const int* __restrict__ qv, const __nv_bfloat16* __restrict__ vsc,
              const __nv_bfloat16* __restrict__ vzp, const __nv_bfloat16* __restrict__ qcos,
              const __nv_bfloat16* __restrict__ qsin, const __nv_bfloat16* __restrict__ kcos,
              const __nv_bfloat16* __restrict__ ksin, __nv_bfloat16* __restrict__ out) {
    __shared__ float qr[kD], lg[kS], red[8];
    const int h = blockIdx.x, t = threadIdx.x, warp = t >> 5, lane = t & 31;
    if (t < kD) {
        const float x = __bfloat162float(q[h * kD + t]);
        const float y = t < kD / 2 ? -__bfloat162float(q[h * kD + t + kD / 2]) : __bfloat162float(q[h * kD + t - kD / 2]);
        qr[t] = bf_round(bf_round(x * __bfloat162float(qcos[t])) + bf_round(y * __bfloat162float(qsin[t])));
    }
    __syncthreads();
    const float scale_log2e = 1.4426950408889634f * rsqrtf((float)kD);
    float mw = -INFINITY;
    for (int s = warp; s < kS; s += 8) {
        const size_t row = (size_t)h * kS + s;
        const float z = __bfloat162float(kzp[row]);
        float dot = 0.f;
        for (int d = lane; d < kD; d += 32) {
            const int dp = d < kD / 2 ? d + kD / 2 : d - kD / 2;
            const float sn = __bfloat162float(ksin[s * kD + dp]);
            const float e = qr[d] * __bfloat162float(kcos[s * kD + d]) + qr[dp] * (d < kD / 2 ? sn : -sn);
            dot = fmaf((float)qk[row * kD + d] - z, e, dot);
        }
        for (int o = 16; o > 0; o >>= 1) dot += __shfl_xor_sync(0xffffffffu, dot, o);
        dot = dot * __bfloat162float(ksc[row]) * scale_log2e;
        if (lane == 0) lg[s] = dot;
        mw = fmaxf(mw, dot);
    }
    if (lane == 0) red[warp] = mw;
    __syncthreads();
    float M = red[0];
    for (int i = 1; i < 8; i++) M = fmaxf(M, red[i]);
    __syncthreads();
    float l = 0.f;
    for (int s = t; s < kS; s += 256) { const float p = exp2f(lg[s] - M); l += p; lg[s] = p; }
    for (int o = 16; o > 0; o >>= 1) l += __shfl_xor_sync(0xffffffffu, l, o);
    if (lane == 0) red[warp] = l;
    __syncthreads();
    float L = 0.f;
    for (int i = 0; i < 8; i++) L += red[i];
    if (t < kD) {
        float acc = 0.f;
        for (int s = 0; s < kS; s++) {
            const size_t row = (size_t)h * kS + s;
            acc = fmaf(lg[s] * __bfloat162float(vsc[row]), (float)qv[row * kD + t] - __bfloat162float(vzp[row]), acc);
        }
        out[h * kD + t] = __float2bfloat16_rn(acc / L);
    }
}

}

extern "C" void kernel_launch(void* const* d_in, const int* in_sizes, int n_in, void* d_out, int out_size) {
    const __nv_bfloat16* q = (const __nv_bfloat16*)d_in[0];
    const int* qk = (const int*)d_in[1];
    const __nv_bfloat16* ksc = (const __nv_bfloat16*)d_in[2];
    const __nv_bfloat16* kzp = (const __nv_bfloat16*)d_in[3];
    const int* qv = (const int*)d_in[4];
    const __nv_bfloat16* vsc = (const __nv_bfloat16*)d_in[5];
    const __nv_bfloat16* vzp = (const __nv_bfloat16*)d_in[6];
    const __nv_bfloat16* qcos = (const __nv_bfloat16*)d_in[7];
    const __nv_bfloat16* qsin = (const __nv_bfloat16*)d_in[8];
    const __nv_bfloat16* kcos = (const __nv_bfloat16*)d_in[9];
    const __nv_bfloat16* ksin = (const __nv_bfloat16*)d_in[10];

    typedef CUresult (*EncodeFn)(CUtensorMap*, CUtensorMapDataType, cuuint32_t, void*, const cuuint64_t*, const cuuint64_t*,
                                 const cuuint32_t*, const cuuint32_t*, CUtensorMapInterleave, CUtensorMapSwizzle,
                                 CUtensorMapL2promotion, CUtensorMapFloatOOBfill);
    static EncodeFn encode = nullptr;
    static int by_sm = 0;
    static int mode = 0;
    if (!mode) {
        int dev = 0, sms = 0, occ = 0;
        cudaGetDevice(&dev);
        cudaDeviceGetAttribute(&sms, cudaDevAttrMultiProcessorCount, dev);
        cudaError_t e = cudaFuncSetAttribute(attn_kernel, cudaFuncAttributeMaxDynamicSharedMemorySize, kSmemBytes);
        if (e == cudaSuccess) e = cudaOccupancyMaxActiveBlocksPerMultiprocessor(&occ, attn_kernel, kThreads, kSmemBytes);
        void* fn = nullptr;
        cudaDriverEntryPointQueryResult qr;
        if (e == cudaSuccess) e = cudaGetDriverEntryPoint("cuTensorMapEncodeTiled", &fn, cudaEnableDefault, &qr);
        encode = (EncodeFn)fn;
        mode = (e == cudaSuccess && fn && occ * sms >= kGrid) ? 1 : 2;
        (void)cudaGetLastError();
        by_sm = sms == kGrid && occ == 1;
    }
    CUtensorMap tmv;
    bool fast = mode == 1;
    if (fast) {
        const cuuint64_t dims[2] = {(cuuint64_t)kD, (cuuint64_t)kNH * kS}, strides[1] = {(cuuint64_t)kRowBytes};
        const cuuint32_t box[2] = {(cuuint32_t)kFW, (cuuint32_t)(kFRows / kFBoxes)}, es[2] = {1, 1};
        fast = encode(&tmv, CU_TENSOR_MAP_DATA_TYPE_INT32, 2, (void*)qv, dims, strides, box, es, CU_TENSOR_MAP_INTERLEAVE_NONE,
                      CU_TENSOR_MAP_SWIZZLE_NONE, CU_TENSOR_MAP_L2_PROMOTION_L2_128B, CU_TENSOR_MAP_FLOAT_OOB_FILL_NONE) == CUDA_SUCCESS;
    }
    if (fast)
        attn_kernel<<<kGrid, kThreads, kSmemBytes>>>(Scalars{{ksc, kzp, vsc, vzp}}, qk, by_sm, kcos, ksin, qv, q, qcos, qsin,
                                                     (__nv_bfloat16*)d_out, tmv);
    else
        attn_fallback<<<kNH, 256>>>(q, qk, ksc, kzp, qv, vsc, vzp, qcos, qsin, kcos, ksin, (__nv_bfloat16*)d_out);
}
```

```cpp
#include <cuda_runtime.h>
#include <cuda.h>
#include <cuda_bf16.h>
#include <stdint.h>

namespace {

constexpr int kB = 8, kH = 32, kS = 2048, kD = 192;
constexpr int kNH = kB * kH;
constexpr int kTeams = 4;
constexpr int kSlots = 32;
constexpr int kRows = kS / kSlots;
constexpr int kRounds = kNH / kTeams;
constexpr int kStream = kTeams * kSlots;
constexpr int kGrid = kStream + kTeams;
constexpr int kCW = 16;
constexpr int kR = kRows / kCW;
constexpr int kNP = 2;
constexpr int kThreads = (kCW + 2 + kNP) * 32;
constexpr int kRowBytes = kD * 4;
constexpr int kChunk = kRows * kRowBytes;
constexpr int kNS = 3;
constexpr int kHalf = kChunk / 2;
constexpr int kHRows = kRows / 2;
constexpr int kLead = 365;
constexpr int kLeadDef = 430;
constexpr int kRampEnd = 12, kRampStep = 70;
constexpr int kQuick = 20;
constexpr int kSleep = 200;
constexpr int kPR = 12;
constexpr int kScStride = 196;
constexpr int kOffScal = kNS * kChunk;
constexpr int kOffQ = kOffScal + kRounds * 4 * kRows * 2;
constexpr int kOffSc = kOffQ + kRounds * kD * 2;
constexpr int kOffBar = kOffSc + 2 * kCW * kScStride * 4;
constexpr int kF = 3;
constexpr int kFG = 4;
constexpr int kFW = kD / kFG;
constexpr int kFRows = kRows * kFG;
constexpr int kFHeads = kSlots / kFG;
constexpr int kDef0 = 16;
constexpr int kEarly = 4;
constexpr int kFBoxes = 16;
constexpr int kPrep = 40;
constexpr int kOffW = kOffScal;
constexpr int kOffFin = kOffW + kF * kFRows * 4;
constexpr int kPartStride = 20;
constexpr int kOffPart = kOffFin + kFW * 4;
constexpr int kOffMisc = kOffBar + (4 * kNS + 6 + kF * kFBoxes) * 8;
constexpr int kOffMax = kOffMisc + 32;
constexpr int kSmemBytes = kOffMax + 4 * kCW * 4;
constexpr int kRecWords = 112;
constexpr int kMG = 6;
static_assert(kNS >= 3, "ring");
static_assert(kOffBar % 8 == 0 && kOffSc % 16 == 0 && kOffMax % 16 == 0, "alignment");
static_assert(kPR % kMG == 0, "ring");
static_assert(kLead >= kStream && kS == kFHeads * kFRows && kFHeads == 8, "schedule");
static_assert(kSmemBytes <= 232448, "smem");
static_assert(kDef0 + kFHeads < kPrep && kPrep + 16 + 3 < kRounds && kEarly + kF * kFBoxes + 3 < kRounds && kOffPart <= kOffScal + (kPrep - 2) * 4 * kRows * 2 &&
              kOffPart + kF * kFW * kPartStride * 4 <= kOffScal + (kRounds - 2) * 4 * kRows * 2 && kF <= kNS && kFBoxes == kCW, "deferred rounds");

__device__ __align__(128) unsigned long long g_rec[kPR * kStream * kRecWords];
__device__ __align__(128) unsigned long long g_pre[kTeams * kFHeads * kRecWords];
__device__ __align__(128) unsigned long long g_lg[kTeams * kFHeads * kF * kFRows];
__device__ __align__(8192) unsigned int g_prog[kNP * 1024];
__device__ __align__(128) unsigned int g_epoch;
__device__ __align__(128) unsigned int g_arrive;
__device__ __align__(128) unsigned int g_mdone[kTeams * kMG * 32];

constexpr int kSpin = 1 << 24;

__device__ __forceinline__ uint32_t s2u(const void* p) { return (uint32_t)__cvta_generic_to_shared(p); }
__device__ __forceinline__ void mbar_init(uint32_t a, int c) {
    asm volatile("mbarrier.init.shared::cta.b64 [%0], %1;" ::"r"(a), "r"(c));
}
__device__ __forceinline__ void mbar_wait(uint32_t a, uint32_t ph) {
    uint32_t ok;
    for (int it = 0;; it++) {
        asm volatile(
            "{\n.reg .pred p;\nmbarrier.try_wait.parity.shared::cta.b64 p, [%1], %2;\nselp.u32 %0, 1, 0, p;\n}"
            : "=r"(ok) : "r"(a), "r"(ph) : "memory");
        if (ok) break;
        if (it > kSpin) __trap();
    }
}
__device__ __forceinline__ void mbar_arrive(uint32_t a) {
    asm volatile("mbarrier.arrive.shared::cta.b64 _, [%0];" ::"r"(a) : "memory");
}
__device__ __forceinline__ void mbar_expect(uint32_t a, uint32_t bytes) {
    asm volatile("mbarrier.arrive.expect_tx.shared::cta.b64 _, [%0], %1;" ::"r"(a), "r"(bytes) : "memory");
}
__device__ __forceinline__ void bulk_g2s_stream(uint32_t dst, const void* src, uint32_t bytes, uint32_t mbar, uint64_t pol) {
    asm volatile("cp.async.bulk.shared::cluster.global.mbarrier::complete_tx::bytes.L2::cache_hint [%0], [%1], %2, [%3], %4;"
                 ::"r"(dst), "l"(src), "r"(bytes), "r"(mbar), "l"(pol) : "memory");
}
__device__ __forceinline__ void bulk_g2s(uint32_t dst, const void* src, uint32_t bytes, uint32_t mbar) {
    asm volatile("cp.async.bulk.shared::cluster.global.mbarrier::complete_tx::bytes [%0], [%1], %2, [%3];"
                 ::"r"(dst), "l"(src), "r"(bytes), "r"(mbar) : "memory");
}
__device__ __forceinline__ void cp16(uint32_t dst, const void* src) {
    asm volatile("cp.async.cg.shared.global [%0], [%1], 16;" ::"r"(dst), "l"(src) : "memory");
}
__device__ __forceinline__ float bf_lo(uint32_t u) { return __uint_as_float(u << 16); }
__device__ __forceinline__ float bf_hi(uint32_t u) { return __uint_as_float(u & 0xffff0000u); }
__device__ __forceinline__ float bf_round(float x) { return __bfloat162float(__float2bfloat16_rn(x)); }
__device__ __forceinline__ uint32_t ld_pair(const __nv_bfloat16* p) {
    return __ldg(reinterpret_cast<const uint32_t*>(p));
}
__device__ __forceinline__ unsigned int ld_relaxed(const unsigned int* p) {
    unsigned int v;
    asm volatile("ld.relaxed.gpu.global.u32 %0, [%1];" : "=r"(v) : "l"(p) : "memory");
    return v;
}
__device__ __forceinline__ unsigned long long pack_rec(float a, float b, uint32_t tag) {
    const uint32_t x = (__float_as_uint(a) & ~15u) | (tag & 15u), y = (__float_as_uint(b) & ~15u) | (tag >> 4);
    return ((unsigned long long)y << 32) | x;
}
__device__ __forceinline__ void st_rec(unsigned long long* p, float a, float b, uint32_t tag) {
    asm volatile("st.relaxed.gpu.global.b64 [%0], %1;" ::"l"(p), "l"(pack_rec(a, b, tag)) : "memory");
}
__device__ __forceinline__ float rec_lo(unsigned long long w) { return __uint_as_float((uint32_t)w & ~15u); }
__device__ __forceinline__ float rec_hi(unsigned long long w) { return __uint_as_float((uint32_t)(w >> 32) & ~15u); }
__device__ __forceinline__ unsigned long long ld_rec1(const unsigned long long* p) {
    unsigned long long x;
    asm volatile("ld.relaxed.gpu.global.b64 %0, [%1];" : "=l"(x) : "l"(p) : "memory");
    return x;
}
__device__ __forceinline__ void ld_rec2(const unsigned long long* p, unsigned long long& x, unsigned long long& y) {
    asm volatile("ld.relaxed.gpu.global.v2.b64 {%0, %1}, [%2];" : "=l"(x), "=l"(y) : "l"(p) : "memory");
}
__device__ __forceinline__ uint32_t rec_bad(unsigned long long w, uint32_t tlo, uint32_t thi) {
    return (((uint32_t)w ^ tlo) | ((uint32_t)(w >> 32) ^ thi)) & 15u;
}
__device__ __forceinline__ void st_ml(unsigned long long* p, float m, float l, uint32_t tag) {
    const uint32_t y = ((__float_as_uint(l) + 0x80u) & ~0xffu) | tag;
    asm volatile("st.relaxed.gpu.global.b64 [%0], %1;" ::"l"(p), "l"(((unsigned long long)y << 32) | __float_as_uint(m)) : "memory");
}
__device__ __forceinline__ uint32_t ml_bad(unsigned long long w, uint32_t tag) { return ((uint32_t)(w >> 32) ^ tag) & 0xffu; }
__device__ __forceinline__ float ml_m(unsigned long long w) { return __uint_as_float((uint32_t)w); }
__device__ __forceinline__ float ml_l(unsigned long long w) { return __uint_as_float((uint32_t)(w >> 32) & ~0xffu); }
__device__ __forceinline__ float warp_max(float v) {
    const int b = __float_as_int(v);
    const int k = __reduce_max_sync(0xffffffffu, b ^ ((b >> 31) & 0x7fffffff));
    return __int_as_float(k ^ ((k >> 31) & 0x7fffffff));
}
__device__ __forceinline__ uint32_t round_tag(unsigned int epoch, int r) {
    constexpr unsigned kUses = (kRounds + kPR - 1) / kPR;
    return (epoch * kUses + (unsigned)(r / kPR)) % 255u + 1u;
}

__device__ __forceinline__ void rotate_q(uint32_t* qrow, int p, uint32_t c_lo, uint32_t c_hi, uint32_t s_lo, uint32_t s_hi) {
    const uint32_t lo = qrow[p], hi = qrow[p + 48];
    const float a0 = bf_round(bf_lo(lo) * bf_lo(c_lo)) + bf_round(-bf_lo(hi) * bf_lo(s_lo));
    const float a1 = bf_round(bf_hi(lo) * bf_hi(c_lo)) + bf_round(-bf_hi(hi) * bf_hi(s_lo));
    const float b0 = bf_round(bf_lo(hi) * bf_lo(c_hi)) + bf_round(bf_lo(lo) * bf_lo(s_hi));
    const float b1 = bf_round(bf_hi(hi) * bf_hi(c_hi)) + bf_round(bf_hi(lo) * bf_hi(s_hi));
    const __nv_bfloat162 ua = __floats2bfloat162_rn(a0, a1), ub = __floats2bfloat162_rn(b0, b1);
    qrow[p] = *reinterpret_cast<const uint32_t*>(&ua);
    qrow[p + 48] = *reinterpret_cast<const uint32_t*>(&ub);
}
__device__ __forceinline__ int deferred_to(int blk, int r) {
    return (unsigned)(r - kDef0) < (unsigned)kFHeads ? (blk - kF * (r - kDef0)) & (kFHeads - 1) : kF;
}

__device__ __forceinline__ unsigned role_of_sm(unsigned smid) {
    const unsigned u = smid >> 1;
    const unsigned g = u < 32 ? u & 7 : u < 60 ? 1 + (u - 32) % 7 : u < 62 ? u - 54 : 0;
    const unsigned t = u < 32 ? u >> 3 : u < 60 ? 4 + (u - 32) / 7 : u < 62 ? 8 : u - 58;
    const unsigned lin = 16 * g + (g == 7 ? 2 : 0) + 2 * t + (smid & 1);
    return lin < 2 ? lin + kStream : lin < 48 ? lin - 2 : lin < 50 ? lin + (kStream + 2 - 48) : lin - 4;
}
static_assert(kGrid == 132 && kTeams == 4, "role_of_sm");
struct Scalars { const __nv_bfloat16* p[4]; };

__global__ void __launch_bounds__(kThreads, 1)
attn_kernel(const __grid_constant__ Scalars scal, const int* __restrict__ qk, int by_sm, const __nv_bfloat16* __restrict__ kcos,
            const __nv_bfloat16* __restrict__ ksin, const int* __restrict__ qv, const __nv_bfloat16* __restrict__ q,
            const __nv_bfloat16* __restrict__ qcos, const __nv_bfloat16* __restrict__ qsin,
            __nv_bfloat16* __restrict__ out, const __grid_constant__ CUtensorMap tmv) {
    extern __shared__ __align__(128) unsigned char smem[];
    const int warp = threadIdx.x >> 5, lane = threadIdx.x & 31;
    const uint32_t full0 = s2u(smem + kOffBar), empty0 = full0 + 2 * kNS * 8;
    const uint32_t sfull = empty0 + 2 * kNS * 8, sempty = sfull + 16, mxbar = sempty + 16, fine = mxbar + 16;
    volatile unsigned int* s_misc = reinterpret_cast<volatile unsigned int*>(smem + kOffMisc);
    uint64_t pol = 0;

    if (threadIdx.x == kCW * 32 && blockIdx.x < kStream)
        asm volatile("cp.async.bulk.prefetch.L2.global [%0], %1;"
                     ::"l"(scal.p[blockIdx.x & 3] + (blockIdx.x >> 2) * (kNH * kS * 4 / kStream)), "n"(kNH * kS * 4 / kStream * 2) : "memory");
    unsigned bid = blockIdx.x;
    if (by_sm) {
        unsigned smid, nsm;
        asm volatile("mov.u32 %0, %%smid;" : "=r"(smid));
        asm volatile("mov.u32 %0, %%nsmid;" : "=r"(nsm));
        if (nsm == kGrid) bid = role_of_sm(smid);
    }
    if (threadIdx.x == kCW * 32 && bid < kStream) {
        const int m = bid % kSlots;
        const uint32_t sm0 = s2u(smem);
        for (int i = 0; i < 2 * kNS; i++) mbar_init(full0 + 8 * i, 1);
        asm volatile("fence.mbarrier_init.release.cluster;" ::: "memory");
        asm volatile("createpolicy.fractional.L2::evict_first.b64 %0, 1.0;" : "=l"(pol));
        const int* k0 = qk + (size_t)(bid / kSlots * kS + m * kHRows) * kD;
#pragma unroll
        for (int h = 0; h < 2; h++) {
            mbar_expect(full0 + 16 + 8 * h, kHalf);
            bulk_g2s_stream(sm0 + kChunk + h * kHalf, k0 + h * (kS / 2 * kD), kHalf, full0 + 16 + 8 * h, pol);
        }
#pragma unroll
        for (int h = 0; h < 2; h++) {
            mbar_expect(full0 + 8 * h, kHalf);
            bulk_g2s(sm0 + h * kHalf, kcos + (h * (kS / 2) + m * kHRows) * kD, kHalf / 2, full0 + 8 * h);
            bulk_g2s(sm0 + h * kHalf + kHalf / 2, ksin + (h * (kS / 2) + m * kHRows) * kD, kHalf / 2, full0 + 8 * h);
        }
#pragma unroll
        for (int h = 0; h < 2; h++) {
            mbar_expect(full0 + 32 + 8 * h, kHalf);
            bulk_g2s_stream(sm0 + 2 * kChunk + h * kHalf, k0 + (kTeams * kS + h * (kS / 2)) * kD, kHalf, full0 + 32 + 8 * h, pol);
        }
    }

    if (bid >= kStream) {
        const int team = bid - kStream;
        if (threadIdx.x == 0) s_misc[0] = ld_relaxed(&g_epoch);
        __syncthreads();
        if (threadIdx.x == 0 && atomicAdd(&g_arrive, 1u) == kGrid - 1) { g_arrive = 0u; g_epoch = s_misc[0] + 1u; }
        if (warp >= 3 * kMG) return;
        const int grp = warp / 3, t = threadIdx.x - grp * 96;
        constexpr int kRecBytes = kSlots * kRecWords * 8;
        if (t == 0) {
            mbar_init(s2u(smem + kOffBar) + grp * 8, 1);
            asm volatile("fence.mbarrier_init.release.cluster;" ::: "memory");
        }
        asm volatile("bar.sync %0, 96;" ::"r"(3 + grp) : "memory");
        for (int r = grp; r < kRounds; r += kMG) {
            const int g = r % kMG;
            const int tt = threadIdx.x - g * 96, qd = tt % 48, half = tt / 48;
            const uint32_t tag = round_tag(s_misc[0], r);
            const uint32_t tlo = tag & 15u, thi = tag >> 4;
            const unsigned long long* rec = g_rec + ((size_t)(r % kPR) * kStream + team * kSlots) * kRecWords;
            unsigned long long ml, x[16], y[16];
            {
                const unsigned long long* buf = reinterpret_cast<const unsigned long long*>(smem + g * kRecBytes);
                const uint32_t mb = s2u(smem + kOffBar) + g * 8;
                if (tt < 32) {
                    const int want = r == kRounds - 1 ? kQuick : kSlots;
                    for (int i2 = 0;; i2++) {
                        ml = ld_rec1(rec + lane * kRecWords + 96);
                        if (__popc(__ballot_sync(0xffffffffu, ml_bad(ml, tag) == 0)) >= want) break;
                        if (i2 > kSpin) __trap();
                        __nanosleep(kSleep);
                    }
                    if (tt == 0) {
                        mbar_expect(mb, kRecBytes);
                        bulk_g2s(s2u(buf), rec, kRecBytes, mb);
                    }
                }
                mbar_wait(mb, (r / kMG) & 1);
                ml = buf[lane * kRecWords + 96];
#pragma unroll
                for (int i = 0; i < 16; i++) {
                    const ulonglong2 u = *reinterpret_cast<const ulonglong2*>(buf + (half * 16 + i) * kRecWords + 2 * qd);
                    x[i] = u.x; y[i] = u.y;
                }
                const unsigned long long* po = rec + half * 16 * kRecWords + 2 * qd;
                for (int it = 0;; it++) {
                    uint32_t any = ml_bad(ml, tag);
                    if (any) ml = ld_rec1(rec + lane * kRecWords + 96);
#pragma unroll
                    for (int i = 0; i < 16; i++) {
                        const uint32_t bad = rec_bad(x[i], tlo, thi) | rec_bad(y[i], tlo, thi);
                        if (bad) ld_rec2(po + i * kRecWords, x[i], y[i]);
                        any |= bad;
                    }
                    if (__all_sync(0xffffffffu, any == 0)) break;
                    if (it > kSpin) __trap();
                }
            }
            const float M = ml_m(ml);
            const float MM = warp_max(M);
            const float w = exp2f(M - MM);
            float LL = w * ml_l(ml);
#pragma unroll
            for (int o = 16; o > 0; o >>= 1) LL += __shfl_xor_sync(0xffffffffu, LL, o);
            float4 a = make_float4(0.f, 0.f, 0.f, 0.f);
#pragma unroll
            for (int i = 0; i < 16; i++) {
                const float wi = __shfl_sync(0xffffffffu, w, half * 16 + i);
                a.x = fmaf(wi, rec_lo(x[i]), a.x);
                a.y = fmaf(wi, rec_hi(x[i]), a.y);
                a.z = fmaf(wi, rec_lo(y[i]), a.z);
                a.w = fmaf(wi, rec_hi(y[i]), a.w);
            }
            float* rb = reinterpret_cast<float*>(smem + kMG * kRecBytes) + (2 * g + ((r / kMG) & 1)) * kD + 4 * qd;
            if (half == 1) *reinterpret_cast<float4*>(rb) = a;
            asm volatile("bar.sync %0, 96;" ::"r"(3 + g) : "memory");
            if (half == 0) {
                const float4 u = *reinterpret_cast<float4*>(rb);
                if ((unsigned)(r - kDef0) < (unsigned)kFHeads) {
                    unsigned long long* pre = g_pre + (size_t)(team * kFHeads + r - kDef0) * kRecWords;
                    const uint32_t ptag = s_misc[0] % 255u + 1u;
                    st_rec(pre + 2 * qd, a.x + u.x, a.y + u.y, ptag);
                    st_rec(pre + 2 * qd + 1, a.z + u.z, a.w + u.w, ptag);
                    if (qd == 0) st_ml(pre + 96, MM, LL, ptag);
                } else {
                    const float inv = __fdividef(1.0f, LL);
                    const __nv_bfloat162 o0 = __floats2bfloat162_rn((a.x + u.x) * inv, (a.y + u.y) * inv);
                    const __nv_bfloat162 o1 = __floats2bfloat162_rn((a.z + u.z) * inv, (a.w + u.w) * inv);
                    uint2 ov;
                    ov.x = *reinterpret_cast<const uint32_t*>(&o0);
                    ov.y = *reinterpret_cast<const uint32_t*>(&o1);
                    *reinterpret_cast<uint2*>(out + (size_t)(kTeams * r + team) * kD + 4 * qd) = ov;
                }
            }
            if (tt == 95)
                asm volatile("st.relaxed.gpu.global.u32 [%0], %1;" ::"l"(&g_mdone[(team * kMG + g) * 32]), "r"(s_misc[0] * kRounds + r + 1) : "memory");
        }
        return;
    }

    const int m = bid % kSlots, team = bid / kSlots;
    const int row0 = m * kHRows;

    if (warp == kCW) {
        unsigned int epoch = 0;
        const size_t off0 = ((size_t)team * kS + row0) * kD;
        const uint32_t sm0 = s2u(smem);
        if (lane == 0) {
            epoch = ld_relaxed(&g_epoch);
            s_misc[0] = epoch;
            s_misc[1] = 0;
            for (int j = 0; j < kNP; j++) s_misc[4 + j] = epoch * (kStream * (4 * kRounds - 2));
        }
        __syncwarp();
        asm volatile("bar.sync 2, %0;" ::"n"(kThreads) : "memory");
        if (lane == 0) {
            unsigned int cum = epoch * (kStream * (4 * kRounds - 2)) + 4 * kStream;
            int use0 = kNS, use1 = kNS;
            const int* kp = qk + off0;
            const int* vp = qv + off0;
            for (int ph2 = 4; ph2 < 2 * (2 * kRounds + kF); ph2++) {
                const int p = ph2 >> 1, h = ph2 & 1;
                const bool isv = (p & 1) == 0 || p == 2 * kRounds - 1;
                const int r = p == 2 * kRounds - 1 ? kRounds - 1 : isv ? (p >> 1) - 1 : (p + 1) >> 1;
                const uint32_t dm = (isv && (unsigned)(r - kDef0) < (unsigned)kFHeads)
                                        ? ((((1u << kF) - 1) * 0x101u << ((kF * (r - kDef0)) & (kFHeads - 1))) >> (8 + 4 * h)) & 15u : 0u;
                const unsigned int need = cum - max(kRampEnd - ph2, 0) * kRampStep -
                    ((unsigned)(ph2 - (4 * kDef0 + 4)) < (unsigned)(4 * kFHeads + 2) ? kLeadDef : kLead);
                cum += kStream - (kStream / 4) * __popc(dm);
                const bool skip = (dm >> (m / 8)) & 1;
                const int u = h ? use1 : use0;
                const int slot = u >= kNS ? u - kNS : u;
                const uint32_t dst = sm0 + slot * kChunk + h * kHalf, fullb = full0 + 16 * slot + 8 * h;
                const int* src = (isv ? vp : kp) + (size_t)(r * kTeams * kS + h * (kS / 2)) * kD;
                if (!skip) {
                    const int un = u + 1 == 2 * kNS ? 0 : u + 1;
                    if (h) use1 = un; else use0 = un;
                    mbar_wait(fullb + 2 * kNS * 8, u >= kNS ? 0 : 1);
                    if (p < 2 * kRounds) mbar_expect(fullb, kHalf);
                }
                asm volatile("" ::"l"(src), "r"(dst) : "memory");
                if (!skip)
                    for (int it = 0;; it++) {
                        uint32_t x, y;
                        asm volatile("ld.volatile.shared.v2.u32 {%0, %1}, [%2];" : "=r"(x), "=r"(y) : "r"(sm0 + kOffMisc + 16) : "memory");
                        if ((int)((x - need) & (y - need)) >= 0) break;
                        if (it > 16 * kSpin) __trap();
                    }
                if (p >= 2 * kRounds || skip) {
                    const int hi = m / kFG;
                    const int row = (kTeams * (kDef0 + hi) + team) * kS + ((kF * hi + p - 2 * kRounds) & (kFHeads - 1)) * kFRows + h * (kFRows / 2);
                    const uint32_t fb = fine + 8 * (kFBoxes / 2) * (ph2 - 4 * kRounds);
#pragma unroll 1
                    for (int w = 0; w < kFBoxes / 2; w++)
                        asm volatile("{\n.reg .pred p;\nsetp.ne.u32 p, %6, 0;\n"
                                     "@p cp.async.bulk.tensor.2d.shared::cluster.global.tile.mbarrier::complete_tx::bytes.L2::cache_hint [%0], [%1, {%2, %3}], [%4], %5;\n}"
                                     ::"r"(dst + w * (kChunk / kFBoxes)), "l"(&tmv), "r"((m % kFG) * kFW), "r"(row + w * (kFRows / kFBoxes)),
                                       "r"(fb + 8 * w), "l"(pol), "r"((uint32_t)!skip) : "memory");
                } else {
                    bulk_g2s_stream(dst, src, kHalf, fullb, pol);
                }
            }
            s_misc[1] = 1;
        }
    } else if (warp >= kCW + 2) {
        asm volatile("bar.sync 2, %0;" ::"n"(kThreads) : "memory");
        if (lane == 0) {
            const int j = warp - (kCW + 2);
            for (int it = 0; !s_misc[1]; it++) {
                s_misc[4 + j] = ld_relaxed(g_prog + j * 1024);
                if (it > kSpin) __trap();
            }
        }
    } else if (warp == kCW + 1) {
        {
            if (lane < 2 * kNS + 6) mbar_init(empty0 + 8 * lane, lane < 2 * kNS ? kCW / 2 : (lane >= 2 * kNS + 2 && lane < 2 * kNS + 4) ? 1 : kCW);
            asm volatile("fence.mbarrier_init.release.cluster;" ::: "memory");
        }
        asm volatile("bar.sync 2, %0;" ::"n"(kThreads) : "memory");
        const unsigned int epoch = s_misc[0];
        if (lane == 0 && atomicAdd(&g_arrive, 1u) == kGrid - 1) { g_arrive = 0u; g_epoch = epoch + 1u; }
        {
            const uint32_t sm0 = s2u(smem);
            const __nv_bfloat16* src = scal.p[lane >> 3] + (size_t)team * kS + row0 + (lane & 4) * (kS / 8) + (lane & 3) * 8;
            const __nv_bfloat16* qs = q + team * kD + lane * 8;
#pragma unroll 1
            for (int r = kEarly; r < kRounds; r++) {
                cp16(sm0 + kOffScal + r * 512 + lane * 16, src + (size_t)r * (kTeams * kS));
                if (lane < 24) cp16(sm0 + kOffQ + r * (kD * 2) + lane * 16, qs + r * (kTeams * kD));
                if (r == 2 * kEarly - 1 || r == kRounds - 1) asm volatile("cp.async.commit_group;" ::: "memory");
            }
        }
        uint32_t cs[2][4];
#pragma unroll
        for (int i = 0; i < 2; i++) {
            const int p = (lane + 32 * i) % 48;
            cs[i][0] = ld_pair(qcos + 2 * p); cs[i][1] = ld_pair(qcos + 2 * p + 96);
            cs[i][2] = ld_pair(qsin + 2 * p); cs[i][3] = ld_pair(qsin + 2 * p + 96);
        }
        asm volatile("cp.async.wait_group 1;" ::: "memory");
        __syncwarp();
        for (int r = 0; r < kRounds; r++) {
            const float* sc = reinterpret_cast<const float*>(smem + kOffSc) + (r & 1) * (kCW * kScStride);
            const uint32_t tag = round_tag(epoch, r);
            unsigned long long* rec = g_rec + ((size_t)(r % kPR) * kStream + team * kSlots + m) * kRecWords;
            if (r >= kEarly && r < kEarly + kF * kFBoxes && lane == 0) {
                mbar_init(fine + 8 * (r - kEarly), 1);
                asm volatile("fence.mbarrier_init.release.cluster;" ::: "memory");
                mbar_expect(fine + 8 * (r - kEarly), kChunk / kFBoxes);
                asm volatile("fence.proxy.async.shared::cta;" ::: "memory");
            }
            if (r == kPrep + m / 2) {
                const unsigned long long* pre = g_pre + (size_t)(team * kFHeads + m / kFG) * kRecWords;
                const unsigned long long* lgp = g_lg + (size_t)(team * kFHeads + m / kFG) * (kF * kFRows);
                const uint32_t ptag = epoch % 255u + 1u;
                unsigned long long ml, po;
                for (int it = 0;; it++) {
                    ml = ld_rec1(pre + 96);
                    po = ld_rec1(pre + (m % kFG) * (kFW / 2) + lane % (kFW / 2));
                    if (!(ml_bad(ml, ptag) | rec_bad(po, ptag & 15u, ptag >> 4))) break;
                    if (it > kSpin) __trap();
                }
                const float inv = 1.0f / ml_l(ml);
                if (lane < kFW / 2) {
                    reinterpret_cast<float*>(smem + kOffFin)[lane] = rec_lo(po) * inv;
                    reinterpret_cast<float*>(smem + kOffFin)[kFW / 2 + lane] = rec_hi(po) * inv;
                }
#pragma unroll 1
                for (int c = 0; c < kF; c++) {
                    unsigned long long u[8];
                    for (int it = 0;; it++) {
                        uint32_t bad = 0;
#pragma unroll
                        for (int k = 0; k < 8; k++) {
                            u[k] = ld_rec1(lgp + c * kFRows + 32 * k + lane);
                            bad |= ml_bad(u[k], ptag);
                        }
                        if (!bad) break;
                        if (it > kSpin) __trap();
                    }
#pragma unroll
                    for (int k = 0; k < 8; k++)
                        reinterpret_cast<float*>(smem + kOffW)[c * kFRows + 32 * k + lane] = ml_l(u[k]) * exp2f(ml_m(u[k]) - ml_m(ml)) * inv;
                }
                __syncwarp();
            }
            if (r == kRounds - 3 && lane == 0) asm volatile("prefetch.tensormap [%0];" ::"l"(&tmv) : "memory");
            if (r == kEarly) {
                asm volatile("cp.async.wait_all;" ::: "memory");
                __syncwarp();
            }
            if (r + kEarly < kRounds) {
                uint32_t* qrow = reinterpret_cast<uint32_t*>(smem + kOffQ + (r + kEarly) * (kD * 2));
                rotate_q(qrow, lane, cs[0][0], cs[0][1], cs[0][2], cs[0][3]);
                if (lane < 16) rotate_q(qrow, lane + 32, cs[1][0], cs[1][1], cs[1][2], cs[1][3]);
            }
            if (r >= kPR) {
                const unsigned int* mdone = &g_mdone[(team * kMG + r % kMG) * 32];
                const unsigned int need = epoch * kRounds + r - kPR + 1;
                for (int it = 0; (int)(ld_relaxed(mdone) - need) < 0; it++)
                    if (it > kSpin) __trap();
            }
            mbar_wait(sfull + 8 * (r & 1), (r >> 1) & 1);
            const float M = sc[0];
            float L = lane < kCW ? sc[lane * kScStride + 1] : 0.f;
            float acc[2][6];
#pragma unroll
            for (int ww = 0; ww < kCW; ww++) {
#pragma unroll
                for (int j = 0; j < 3; j++) {
                    const float2 t = *reinterpret_cast<const float2*>(sc + ww * kScStride + 4 + 64 * j + 2 * lane);
                    acc[ww & 1][2 * j] = ww < 2 ? t.x : acc[ww & 1][2 * j] + t.x;
                    acc[ww & 1][2 * j + 1] = ww < 2 ? t.y : acc[ww & 1][2 * j + 1] + t.y;
                }
                if ((ww & 3) == 3 && ww < 15) L += __shfl_xor_sync(0xffffffffu, L, 8 >> (ww >> 2));
            }
            L += __shfl_xor_sync(0xffffffffu, L, 1);
#pragma unroll
            for (int j = 0; j < 3; j++)
                st_rec(rec + 32 * j + lane, acc[0][2 * j] + acc[1][2 * j], acc[0][2 * j + 1] + acc[1][2 * j + 1], tag);
            if (lane == 0) st_ml(rec + 96, M, L, tag);
            __syncwarp();
            if (lane == 0) mbar_arrive(sempty + 8 * (r & 1));
        }
    } else {
        int dp[3];
#pragma unroll
        for (int j = 0; j < 3; j++) dp[j] = (64 * j + 2 * lane + 96) % kD;
        {
            const uint32_t sm0 = s2u(smem);
            if (warp < kEarly) {
                cp16(sm0 + kOffScal + threadIdx.x * 16, scal.p[lane >> 3] + (size_t)(kTeams * warp + team) * kS + row0 + (lane & 4) * (kS / 8) + (lane & 3) * 8);
            } else if (warp < 2 * kEarly && lane < 24) {
                cp16(sm0 + kOffQ + (warp - kEarly) * (kD * 2) + lane * 16, q + (size_t)(kTeams * (warp - kEarly) + team) * kD + lane * 8);
            }
            asm volatile("cp.async.commit_group;" ::: "memory");
        }
        const int p = threadIdx.x % 48, g = threadIdx.x / 48;
        const uint32_t c_lo = ld_pair(qcos + 2 * p), c_hi = ld_pair(qcos + 2 * p + 96);
        const uint32_t s_lo = ld_pair(qsin + 2 * p), s_hi = ld_pair(qsin + 2 * p + 96);
        float kc[kR][6], ks[kR][6];
        asm volatile("bar.sync 2, %0;" ::"n"(kThreads) : "memory");
        const int half = warp / (kCW / 2);
        const uint32_t fullh = full0 + 8 * half, emptyh = empty0 + 8 * half;
        mbar_wait(fullh, 0);
#pragma unroll
        for (int i = 0; i < kR; i++) {
            const unsigned char* cb = smem + half * (kHalf / 2) + (warp * kR + i) * (kD * 2);
#pragma unroll
            for (int j = 0; j < 3; j++) {
                const uint32_t uc = *reinterpret_cast<const uint32_t*>(cb + 128 * j + 4 * lane);
                const uint32_t us = *reinterpret_cast<const uint32_t*>(cb + kHalf / 2 + 2 * dp[j]);
                kc[i][2 * j] = bf_lo(uc); kc[i][2 * j + 1] = bf_hi(uc);
                const float sg = (j == 0 || (j == 1 && lane < 16)) ? 1.f : -1.f;
                ks[i][2 * j] = sg * bf_lo(us); ks[i][2 * j + 1] = sg * bf_hi(us);
            }
        }
        __syncwarp();
        if (lane == 0) mbar_arrive(emptyh);
        asm volatile("cp.async.wait_group 0;" ::: "memory");
        asm volatile("bar.sync 1, %0;" ::"n"(kCW * 32) : "memory");
        if (g < kEarly) rotate_q(reinterpret_cast<uint32_t*>(smem + kOffQ + g * (kD * 2)), p, c_lo, c_hi, s_lo, s_hi);
        asm volatile("bar.sync 1, %0;" ::"n"(kCW * 32) : "memory");
        const float scale_log2e = 1.4426950408889634f * rsqrtf((float)kD);
        float* my0 = reinterpret_cast<float*>(smem + kOffSc) + warp * kScStride;

        float* s_max = reinterpret_cast<float*>(smem + kOffMax);
        int slot = 1;
        uint32_t ph = 0;
        float lgc[kR] = {0.f, 0.f, 0.f, 0.f};
        for (int it = 0; it <= kRounds; it++) {
            float lg[kR];
            if (it < kRounds) {
                float qa[6], qb[6];
#pragma unroll
                for (int j = 0; j < 3; j++) {
                    const uint32_t qo = *reinterpret_cast<const uint32_t*>(smem + kOffQ + it * (kD * 2) + 2 * (64 * j + 2 * lane));
                    const uint32_t qp = *reinterpret_cast<const uint32_t*>(smem + kOffQ + it * (kD * 2) + 2 * dp[j]);
                    qa[2 * j] = bf_lo(qo); qa[2 * j + 1] = bf_hi(qo);
                    qb[2 * j] = bf_lo(qp); qb[2 * j + 1] = bf_hi(qp);
                }
                const unsigned char* sp = smem + kOffScal + it * (4 * kRows * 2) + warp * (kR * 2);
                const uint2 uks = *reinterpret_cast<const uint2*>(sp);
                const uint2 ukz = *reinterpret_cast<const uint2*>(sp + kRows * 2);
                const float kz[4] = {bf_lo(ukz.x), bf_hi(ukz.x), bf_lo(ukz.y), bf_hi(ukz.y)};
                const float sk[4] = {bf_lo(uks.x), bf_hi(uks.x), bf_lo(uks.y), bf_hi(uks.y)};
                mbar_wait(fullh + 16 * slot, ph);
                if ((threadIdx.x & 255) < kNP) asm volatile("red.relaxed.gpu.global.add.u32 [%0], 1;" ::"l"(g_prog + lane * 1024) : "memory");
                const unsigned char* kb = smem + slot * kChunk + warp * (kR * kRowBytes) + lane * 8;
#pragma unroll
                for (int i = 0; i < kR; i++) {
                    float dot = 0.f;
#pragma unroll
                    for (int j = 0; j < 3; j++) {
                        const int2 kk = *reinterpret_cast<const int2*>(kb + i * kRowBytes + 256 * j);
                        const float e0 = qa[2 * j] * kc[i][2 * j] + qb[2 * j] * ks[i][2 * j];
                        const float e1 = qa[2 * j + 1] * kc[i][2 * j + 1] + qb[2 * j + 1] * ks[i][2 * j + 1];
                        dot = fmaf((float)kk.x - kz[i], e0, dot);
                        dot = fmaf((float)kk.y - kz[i], e1, dot);
                    }
                    lg[i] = dot;
                }
                __syncwarp();
                if (lane == 0) mbar_arrive(emptyh + 16 * slot);
                if (++slot == kNS) { slot = 0; ph ^= 1; }
#pragma unroll
                for (int o = 16; o > 0; o >>= 1) {
#pragma unroll
                    for (int i = 0; i < kR; i++) lg[i] += __shfl_xor_sync(0xffffffffu, lg[i], o);
                }
                float mw = -INFINITY;
#pragma unroll
                for (int i = 0; i < kR; i++) {
                    lg[i] = lg[i] * sk[i] * scale_log2e;
                    mw = fmaxf(mw, lg[i]);
                }
                if (lane == 0) {
                    s_max[(it & 3) * kCW + warp] = mw;
                    mbar_arrive(mxbar + 8 * (it & 1));
                }
            }
            if (it > 0) {
                const int r = it - 1;
                float* my = my0 + (r & 1) * (kCW * kScStride);
                const int df = deferred_to(4 * half + m / 8, r);
                const unsigned char* sp = smem + kOffScal + r * (4 * kRows * 2) + warp * (kR * 2);
                const uint2 uvs = *reinterpret_cast<const uint2*>(sp + 2 * kRows * 2);
                const uint2 uvz = *reinterpret_cast<const uint2*>(sp + 3 * kRows * 2);
                const float vz[4] = {bf_lo(uvz.x), bf_hi(uvz.x), bf_lo(uvz.y), bf_hi(uvz.y)};
                const float sv[4] = {bf_lo(uvs.x), bf_hi(uvs.x), bf_lo(uvs.y), bf_hi(uvs.y)};
                mbar_wait(mxbar + 8 * (r & 1), (r >> 1) & 1);
                float M;
                {
                    const float4* pm4 = reinterpret_cast<const float4*>(s_max + (r & 3) * kCW);
                    const float4 m0 = pm4[0], m1 = pm4[1], m2 = pm4[2], m3 = pm4[3];
                    M = fmaxf(fmaxf(fmaxf(fmaxf(m0.x, m0.y), fmaxf(m0.z, m0.w)), fmaxf(fmaxf(m1.x, m1.y), fmaxf(m1.z, m1.w))),
                              fmaxf(fmaxf(fmaxf(m2.x, m2.y), fmaxf(m2.z, m2.w)), fmaxf(fmaxf(m3.x, m3.y), fmaxf(m3.z, m3.w))));
                }
                float lw = 0.f, cz = 0.f, pv[kR];
#pragma unroll
                for (int i = 0; i < kR; i++) {
                    const float p = exp2f(lgc[i] - M);
                    lw += p;
                    pv[i] = p * sv[i];
                    cz = fmaf(pv[i], vz[i], cz);
                }
                mbar_wait(sempty + 8 * (r & 1), ((r >> 1) & 1) ^ 1);
                if (lane == 0) { my[0] = M; my[1] = lw; }
                float acc[6] = {-cz, -cz, -cz, -cz, -cz, -cz};
                if (df < kF) {
                    if (lane < kR)
                        st_ml(g_lg + ((team * kFHeads + r - kDef0) * kF + df) * kFRows + (m % 8) * kHRows + (warp % 8) * kR + lane, M,
                              lane == 0 ? pv[0] : lane == 1 ? pv[1] : lane == 2 ? pv[2] : pv[3], s_misc[0] % 255u + 1u);
                } else {
                    mbar_wait(fullh + 16 * slot, ph);
                    if ((threadIdx.x & 255) < kNP) asm volatile("red.relaxed.gpu.global.add.u32 [%0], 1;" ::"l"(g_prog + lane * 1024) : "memory");
                    const unsigned char* vb = smem + slot * kChunk + warp * (kR * kRowBytes) + lane * 8;
#pragma unroll
                    for (int i = 0; i < kR; i++) {
#pragma unroll
                        for (int j = 0; j < 3; j++) {
                            const int2 vv = *reinterpret_cast<const int2*>(vb + i * kRowBytes + 256 * j);
                            acc[2 * j] = fmaf(pv[i], (float)vv.x, acc[2 * j]);
                            acc[2 * j + 1] = fmaf(pv[i], (float)vv.y, acc[2 * j + 1]);
                        }
                    }
                    __syncwarp();
                    if (lane == 0) mbar_arrive(emptyh + 16 * slot);
                    if (++slot == kNS) { slot = 0; ph ^= 1; }
                }
#pragma unroll
                for (int j = 0; j < 3; j++)
                    *reinterpret_cast<float2*>(my + 4 + 64 * j + 2 * lane) = make_float2(acc[2 * j], acc[2 * j + 1]);
                __syncwarp();
                if (lane == 0) mbar_arrive(sfull + 8 * (r & 1));
            }
#pragma unroll
            for (int i = 0; i < kR; i++) lgc[i] = lg[i];
        }
        {
            const int cp = lane < kFW / 2 ? lane : 0;
            const int ft = threadIdx.x < kFW ? threadIdx.x : 0;
            const float fin = reinterpret_cast<const float*>(smem + kOffFin)[ft];
            __nv_bfloat16* op = out + (size_t)(kTeams * (kDef0 + m / kFG) + team) * kD + (m % kFG) * kFW + 2 * (ft % (kFW / 2)) + ft / (kFW / 2);
            float a0 = 0.f, a1 = 0.f, b0 = 0.f, b1 = 0.f;
#pragma unroll 1
            for (int f = 0; f < kF; f++) {
                const float* sw = reinterpret_cast<const float*>(smem + kOffW) + f * kFRows + (warp >> 2) * 16 + (warp & 3) * 4;
                const unsigned char* vb = smem + slot * kChunk + ((warp >> 2) * 16 + (warp & 3) * 4) * (kFW * 4) + cp * 8;
                const uint32_t fb = fine + (f * kFBoxes + (warp >> 2)) * 8;
                float* part = reinterpret_cast<float*>(smem + kOffPart) + f * (kFW * kPartStride);
                float4 w[4];
#pragma unroll
                for (int k = 0; k < 4; k++) w[k] = *reinterpret_cast<const float4*>(sw + 64 * k);
#pragma unroll
                for (int k = 0; k < 4; k++) {
                    mbar_wait(fb + 32 * k, 0);
                    if ((k & 1) && warp == kCW - 1 && lane < kNP && f < kF - 1) asm volatile("red.relaxed.gpu.global.add.u32 [%0], 1;" ::"l"(g_prog + lane * 1024) : "memory");
                    const int2 v0 = *reinterpret_cast<const int2*>(vb + k * (64 * kFW * 4));
                    const int2 v1 = *reinterpret_cast<const int2*>(vb + k * (64 * kFW * 4) + kFW * 4);
                    const int2 v2 = *reinterpret_cast<const int2*>(vb + k * (64 * kFW * 4) + 2 * kFW * 4);
                    const int2 v3 = *reinterpret_cast<const int2*>(vb + k * (64 * kFW * 4) + 3 * kFW * 4);
                    a0 = fmaf(w[k].x, (float)v0.x, a0); a1 = fmaf(w[k].x, (float)v0.y, a1);
                    b0 = fmaf(w[k].y, (float)v1.x, b0); b1 = fmaf(w[k].y, (float)v1.y, b1);
                    a0 = fmaf(w[k].z, (float)v2.x, a0); a1 = fmaf(w[k].z, (float)v2.y, a1);
                    b0 = fmaf(w[k].w, (float)v3.x, b0); b1 = fmaf(w[k].w, (float)v3.y, b1);
                }
                if (lane < kFW / 2) {
                    part[lane * kPartStride + warp] = a0 + b0;
                    part[(kFW / 2 + lane) * kPartStride + warp] = a1 + b1;
                }
                if (warp >= 2) {
                    asm volatile("bar.arrive %0, %1;" ::"r"(3 + f), "n"(kCW * 32) : "memory");
                } else {
                    asm volatile("bar.sync %0, %1;" ::"r"(3 + f), "n"(kCW * 32) : "memory");
                    const float4* ps = reinterpret_cast<const float4*>(part + ft * kPartStride);
                    const float4 p0 = ps[0], p1 = ps[1], p2 = ps[2], p3 = ps[3];
                    const float sum = (((p0.x + p0.y) + (p0.z + p0.w)) + ((p1.x + p1.y) + (p1.z + p1.w))) +
                                      (((p2.x + p2.y) + (p2.z + p2.w)) + ((p3.x + p3.y) + ((p3.z + p3.w) + fin)));
                    asm volatile("{\n.reg .pred p;\n.reg .b16 h;\nsetp.ne.u32 p, %2, 0;\ncvt.rn.bf16.f32 h, %1;\n@p st.global.b16 [%0], h;\n}"
                                 ::"l"(op), "f"(sum), "r"((uint32_t)(f == kF - 1 && threadIdx.x < kFW)) : "memory");
                }
                if (++slot == kNS) slot = 0;
            }
        }
    }
}

__global__ void __launch_bounds__(256)
attn_fallback(const __nv_bfloat16* __restrict__ q, const int* __restrict__ qk,
              const __nv_bfloat16* __restrict__ ksc, const __nv_bfloat16* __restrict__ kzp,
              const int* __restrict__ qv, const __nv_bfloat16* __restrict__ vsc,
              const __nv_bfloat16* __restrict__ vzp, const __nv_bfloat16* __restrict__ qcos,
              const __nv_bfloat16* __restrict__ qsin, const __nv_bfloat16* __restrict__ kcos,
              const __nv_bfloat16* __restrict__ ksin, __nv_bfloat16* __restrict__ out) {
    __shared__ float qr[kD], lg[kS], red[8];
    const int h = blockIdx.x, t = threadIdx.x, warp = t >> 5, lane = t & 31;
    if (t < kD) {
        const float x = __bfloat162float(q[h * kD + t]);
        const float y = t < kD / 2 ? -__bfloat162float(q[h * kD + t + kD / 2]) : __bfloat162float(q[h * kD + t - kD / 2]);
        qr[t] = bf_round(bf_round(x * __bfloat162float(qcos[t])) + bf_round(y * __bfloat162float(qsin[t])));
    }
    __syncthreads();
    const float scale_log2e = 1.4426950408889634f * rsqrtf((float)kD);
    float mw = -INFINITY;
    for (int s = warp; s < kS; s += 8) {
        const size_t row = (size_t)h * kS + s;
        const float z = __bfloat162float(kzp[row]);
        float dot = 0.f;
        for (int d = lane; d < kD; d += 32) {
            const int dp = d < kD / 2 ? d + kD / 2 : d - kD / 2;
            const float sn = __bfloat162float(ksin[s * kD + dp]);
            const float e = qr[d] * __bfloat162float(kcos[s * kD + d]) + qr[dp] * (d < kD / 2 ? sn : -sn);
            dot = fmaf((float)qk[row * kD + d] - z, e, dot);
        }
        for (int o = 16; o > 0; o >>= 1) dot += __shfl_xor_sync(0xffffffffu, dot, o);
        dot = dot * __bfloat162float(ksc[row]) * scale_log2e;
        if (lane == 0) lg[s] = dot;
        mw = fmaxf(mw, dot);
    }
    if (lane == 0) red[warp] = mw;
    __syncthreads();
    float M = red[0];
    for (int i = 1; i < 8; i++) M = fmaxf(M, red[i]);
    __syncthreads();
    float l = 0.f;
    for (int s = t; s < kS; s += 256) { const float p = exp2f(lg[s] - M); l += p; lg[s] = p; }
    for (int o = 16; o > 0; o >>= 1) l += __shfl_xor_sync(0xffffffffu, l, o);
    if (lane == 0) red[warp] = l;
    __syncthreads();
    float L = 0.f;
    for (int i = 0; i < 8; i++) L += red[i];
    if (t < kD) {
        float acc = 0.f;
        for (int s = 0; s < kS; s++) {
            const size_t row = (size_t)h * kS + s;
            acc = fmaf(lg[s] * __bfloat162float(vsc[row]), (float)qv[row * kD + t] - __bfloat162float(vzp[row]), acc);
        }
        out[h * kD + t] = __float2bfloat16_rn(acc / L);
    }
}

}

extern "C" void kernel_launch(void* const* d_in, const int* in_sizes, int n_in, void* d_out, int out_size) {
    const __nv_bfloat16* q = (const __nv_bfloat16*)d_in[0];
    const int* qk = (const int*)d_in[1];
    const __nv_bfloat16* ksc = (const __nv_bfloat16*)d_in[2];
    const __nv_bfloat16* kzp = (const __nv_bfloat16*)d_in[3];
    const int* qv = (const int*)d_in[4];
    const __nv_bfloat16* vsc = (const __nv_bfloat16*)d_in[5];
    const __nv_bfloat16* vzp = (const __nv_bfloat16*)d_in[6];
    const __nv_bfloat16* qcos = (const __nv_bfloat16*)d_in[7];
    const __nv_bfloat16* qsin = (const __nv_bfloat16*)d_in[8];
    const __nv_bfloat16* kcos = (const __nv_bfloat16*)d_in[9];
    const __nv_bfloat16* ksin = (const __nv_bfloat16*)d_in[10];

    typedef CUresult (*EncodeFn)(CUtensorMap*, CUtensorMapDataType, cuuint32_t, void*, const cuuint64_t*, const cuuint64_t*,
                                 const cuuint32_t*, const cuuint32_t*, CUtensorMapInterleave, CUtensorMapSwizzle,
                                 CUtensorMapL2promotion, CUtensorMapFloatOOBfill);
    static EncodeFn encode = nullptr;
    static int by_sm = 0;
    static int mode = 0;
    if (!mode) {
        int dev = 0, sms = 0, occ = 0;
        cudaGetDevice(&dev);
        cudaDeviceGetAttribute(&sms, cudaDevAttrMultiProcessorCount, dev);
        cudaError_t e = cudaFuncSetAttribute(attn_kernel, cudaFuncAttributeMaxDynamicSharedMemorySize, kSmemBytes);
        if (e == cudaSuccess) e = cudaOccupancyMaxActiveBlocksPerMultiprocessor(&occ, attn_kernel, kThreads, kSmemBytes);
        void* fn = nullptr;
        cudaDriverEntryPointQueryResult qr;
        if (e == cudaSuccess) e = cudaGetDriverEntryPoint("cuTensorMapEncodeTiled", &fn, cudaEnableDefault, &qr);
        encode = (EncodeFn)fn;
        mode = (e == cudaSuccess && fn && occ * sms >= kGrid) ? 1 : 2;
        (void)cudaGetLastError();
        by_sm = sms == kGrid && occ == 1;
    }
    CUtensorMap tmv;
    bool fast = mode == 1;
    if (fast) {
        const cuuint64_t dims[2] = {(cuuint64_t)kD, (cuuint64_t)kNH * kS}, strides[1] = {(cuuint64_t)kRowBytes};
        const cuuint32_t box[2] = {(cuuint32_t)kFW, (cuuint32_t)(kFRows / kFBoxes)}, es[2] = {1, 1};
        fast = encode(&tmv, CU_TENSOR_MAP_DATA_TYPE_INT32, 2, (void*)qv, dims, strides, box, es, CU_TENSOR_MAP_INTERLEAVE_NONE,
                      CU_TENSOR_MAP_SWIZZLE_NONE, CU_TENSOR_MAP_L2_PROMOTION_L2_128B, CU_TENSOR_MAP_FLOAT_OOB_FILL_NONE) == CUDA_SUCCESS;
    }
    if (fast)
        attn_kernel<<<kGrid, kThreads, kSmemBytes>>>(Scalars{{ksc, kzp, vsc, vzp}}, qk, by_sm, kcos, ksin, qv, q, qcos, qsin,
                                                     (__nv_bfloat16*)d_out, tmv);
    else
        attn_fallback<<<kNH, 256>>>(q, qk, ksc, kzp, qv, vsc, vzp, qcos, qsin, kcos, ksin, (__nv_bfloat16*)d_out);
}
```

```cpp
#include <cuda_runtime.h>
#include <cuda.h>
#include <cuda_bf16.h>
#include <stdint.h>

namespace {

constexpr int kB = 8, kH = 32, kS = 2048, kD = 192;
constexpr int kNH = kB * kH;
constexpr int kTeams = 4;
constexpr int kSlots = 32;
constexpr int kRows = kS / kSlots;
constexpr int kRounds = kNH / kTeams;
constexpr int kStream = kTeams * kSlots;
constexpr int kGrid = kStream + kTeams;
constexpr int kCW = 16;
constexpr int kR = kRows / kCW;
constexpr int kNP = 2;
constexpr int kThreads = (kCW + 2 + kNP) * 32;
constexpr int kRowBytes = kD * 4;
constexpr int kChunk = kRows * kRowBytes;
constexpr int kNS = 3;
constexpr int kHalf = kChunk / 2;
constexpr int kHRows = kRows / 2;
constexpr int kLead = 265;
constexpr int kLeadDef = 320;
constexpr int kRampEnd = 12, kRampStep = 70;
constexpr uint32_t kRate = 69, kAhead = 256;
constexpr int kPollSleep = 300;
constexpr int kQuick = 20;
constexpr int kSleep = 200;
constexpr int kPR = 12;
constexpr int kScStride = 196;
constexpr int kOffScal = kNS * kChunk;
constexpr int kOffQ = kOffScal + kRounds * 4 * kRows * 2;
constexpr int kOffSc = kOffQ + kRounds * kD * 2;
constexpr int kOffBar = kOffSc + 2 * kCW * kScStride * 4;
constexpr int kF = 3;
constexpr int kFG = 4;
constexpr int kFW = kD / kFG;
constexpr int kFRows = kRows * kFG;
constexpr int kFHeads = kSlots / kFG;
constexpr int kDef0 = 16;
constexpr int kEarly = 4;
constexpr int kFBoxes = 16;
constexpr int kPrep = 40;
constexpr int kOffW = kOffScal;
constexpr int kOffFin = kOffW + kF * kFRows * 4;
constexpr int kPartStride = 20;
constexpr int kOffPart = kOffFin + kFW * 4;
constexpr int kOffMisc = kOffBar + (4 * kNS + 6 + kF * kFBoxes) * 8;
constexpr int kOffMax = kOffMisc + 32;
constexpr int kSmemBytes = kOffMax + 4 * kCW * 4;
constexpr int kRecWords = 112;
constexpr int kMG = 6;
static_assert(kNS >= 3, "ring");
static_assert(kOffBar % 8 == 0 && kOffSc % 16 == 0 && kOffMax % 16 == 0, "alignment");
static_assert(kPR % kMG == 0, "ring");
static_assert(kNP == 2 && kOffMisc % 16 == 0 && kLead >= kStream && kS == kFHeads * kFRows && kFHeads == 8, "schedule");
static_assert(kSmemBytes <= 232448, "smem");
static_assert(kDef0 + kFHeads < kPrep && kPrep + 16 + 3 < kRounds && kEarly + kF * kFBoxes + 3 < kRounds && kOffPart <= kOffScal + (kPrep - 2) * 4 * kRows * 2 &&
              kOffPart + kF * kFW * kPartStride * 4 <= kOffScal + (kRounds - 2) * 4 * kRows * 2 && kF <= kNS && kFBoxes == kCW, "deferred rounds");

__device__ __align__(128) unsigned long long g_rec[kPR * kStream * kRecWords];
__device__ __align__(128) unsigned long long g_pre[kTeams * kFHeads * kRecWords];
__device__ __align__(128) unsigned long long g_lg[kTeams * kFHeads * kF * kFRows];
__device__ __align__(8192) unsigned int g_prog[kNP * 1024];
__device__ __align__(128) unsigned int g_epoch;
__device__ __align__(128) unsigned int g_arrive;
__device__ __align__(128) unsigned int g_mdone[kTeams * kMG * 32];

constexpr int kSpin = 1 << 24;

__device__ __forceinline__ uint32_t clock32() {
    uint32_t t;
    asm volatile("mov.u32 %0, %%clock;" : "=r"(t)::"memory");
    return t;
}
__device__ __forceinline__ uint32_t s2u(const void* p) { return (uint32_t)__cvta_generic_to_shared(p); }
__device__ __forceinline__ void mbar_init(uint32_t a, int c) {
    asm volatile("mbarrier.init.shared::cta.b64 [%0], %1;" ::"r"(a), "r"(c));
}
__device__ __forceinline__ void mbar_wait(uint32_t a, uint32_t ph) {
    uint32_t ok;
    for (int it = 0;; it++) {
        asm volatile(
            "{\n.reg .pred p;\nmbarrier.try_wait.parity.shared::cta.b64 p, [%1], %2;\nselp.u32 %0, 1, 0, p;\n}"
            : "=r"(ok) : "r"(a), "r"(ph) : "memory");
        if (ok) break;
        if (it > kSpin) __trap();
    }
}
__device__ __forceinline__ void mbar_arrive(uint32_t a) {
    asm volatile("mbarrier.arrive.shared::cta.b64 _, [%0];" ::"r"(a) : "memory");
}
__device__ __forceinline__ void mbar_expect(uint32_t a, uint32_t bytes) {
    asm volatile("mbarrier.arrive.expect_tx.shared::cta.b64 _, [%0], %1;" ::"r"(a), "r"(bytes) : "memory");
}
__device__ __forceinline__ void bulk_g2s_stream(uint32_t dst, const void* src, uint32_t bytes, uint32_t mbar, uint64_t pol) {
    asm volatile("cp.async.bulk.shared::cluster.global.mbarrier::complete_tx::bytes.L2::cache_hint [%0], [%1], %2, [%3], %4;"
                 ::"r"(dst), "l"(src), "r"(bytes), "r"(mbar), "l"(pol) : "memory");
}
__device__ __forceinline__ void bulk_g2s(uint32_t dst, const void* src, uint32_t bytes, uint32_t mbar) {
    asm volatile("cp.async.bulk.shared::cluster.global.mbarrier::complete_tx::bytes [%0], [%1], %2, [%3];"
                 ::"r"(dst), "l"(src), "r"(bytes), "r"(mbar) : "memory");
}
__device__ __forceinline__ void cp16(uint32_t dst, const void* src) {
    asm volatile("cp.async.cg.shared.global [%0], [%1], 16;" ::"r"(dst), "l"(src) : "memory");
}
__device__ __forceinline__ float bf_lo(uint32_t u) { return __uint_as_float(u << 16); }
__device__ __forceinline__ float bf_hi(uint32_t u) { return __uint_as_float(u & 0xffff0000u); }
__device__ __forceinline__ float bf_round(float x) { return __bfloat162float(__float2bfloat16_rn(x)); }
__device__ __forceinline__ uint32_t ld_pair(const __nv_bfloat16* p) {
    return __ldg(reinterpret_cast<const uint32_t*>(p));
}
__device__ __forceinline__ unsigned int ld_relaxed(const unsigned int* p) {
    unsigned int v;
    asm volatile("ld.relaxed.gpu.global.u32 %0, [%1];" : "=r"(v) : "l"(p) : "memory");
    return v;
}
__device__ __forceinline__ unsigned long long pack_rec(float a, float b, uint32_t tag) {
    const uint32_t x = (__float_as_uint(a) & ~15u) | (tag & 15u), y = (__float_as_uint(b) & ~15u) | (tag >> 4);
    return ((unsigned long long)y << 32) | x;
}
__device__ __forceinline__ void st_rec(unsigned long long* p, float a, float b, uint32_t tag) {
    asm volatile("st.relaxed.gpu.global.b64 [%0], %1;" ::"l"(p), "l"(pack_rec(a, b, tag)) : "memory");
}
__device__ __forceinline__ float rec_lo(unsigned long long w) { return __uint_as_float((uint32_t)w & ~15u); }
__device__ __forceinline__ float rec_hi(unsigned long long w) { return __uint_as_float((uint32_t)(w >> 32) & ~15u); }
__device__ __forceinline__ unsigned long long ld_rec1(const unsigned long long* p) {
    unsigned long long x;
    asm volatile("ld.relaxed.gpu.global.b64 %0, [%1];" : "=l"(x) : "l"(p) : "memory");
    return x;
}
__device__ __forceinline__ void ld_rec2(const unsigned long long* p, unsigned long long& x, unsigned long long& y) {
    asm volatile("ld.relaxed.gpu.global.v2.b64 {%0, %1}, [%2];" : "=l"(x), "=l"(y) : "l"(p) : "memory");
}
__device__ __forceinline__ uint32_t rec_bad(unsigned long long w, uint32_t tlo, uint32_t thi) {
    return (((uint32_t)w ^ tlo) | ((uint32_t)(w >> 32) ^ thi)) & 15u;
}
__device__ __forceinline__ void st_ml(unsigned long long* p, float m, float l, uint32_t tag) {
    const uint32_t y = ((__float_as_uint(l) + 0x80u) & ~0xffu) | tag;
    asm volatile("st.relaxed.gpu.global.b64 [%0], %1;" ::"l"(p), "l"(((unsigned long long)y << 32) | __float_as_uint(m)) : "memory");
}
__device__ __forceinline__ uint32_t ml_bad(unsigned long long w, uint32_t tag) { return ((uint32_t)(w >> 32) ^ tag) & 0xffu; }
__device__ __forceinline__ float ml_m(unsigned long long w) { return __uint_as_float((uint32_t)w); }
__device__ __forceinline__ float ml_l(unsigned long long w) { return __uint_as_float((uint32_t)(w >> 32) & ~0xffu); }
__device__ __forceinline__ float warp_max(float v) {
    const int b = __float_as_int(v);
    const int k = __reduce_max_sync(0xffffffffu, b ^ ((b >> 31) & 0x7fffffff));
    return __int_as_float(k ^ ((k >> 31) & 0x7fffffff));
}
__device__ __forceinline__ uint32_t round_tag(unsigned int epoch, int r) {
    constexpr unsigned kUses = (kRounds + kPR - 1) / kPR;
    return (epoch * kUses + (unsigned)(r / kPR)) % 255u + 1u;
}

__device__ __forceinline__ void rotate_q(uint32_t* qrow, int p, uint32_t c_lo, uint32_t c_hi, uint32_t s_lo, uint32_t s_hi) {
    const uint32_t lo = qrow[p], hi = qrow[p + 48];
    const float a0 = bf_round(bf_lo(lo) * bf_lo(c_lo)) + bf_round(-bf_lo(hi) * bf_lo(s_lo));
    const float a1 = bf_round(bf_hi(lo) * bf_hi(c_lo)) + bf_round(-bf_hi(hi) * bf_hi(s_lo));
    const float b0 = bf_round(bf_lo(hi) * bf_lo(c_hi)) + bf_round(bf_lo(lo) * bf_lo(s_hi));
    const float b1 = bf_round(bf_hi(hi) * bf_hi(c_hi)) + bf_round(bf_hi(lo) * bf_hi(s_hi));
    const __nv_bfloat162 ua = __floats2bfloat162_rn(a0, a1), ub = __floats2bfloat162_rn(b0, b1);
    qrow[p] = *reinterpret_cast<const uint32_t*>(&ua);
    qrow[p + 48] = *reinterpret_cast<const uint32_t*>(&ub);
}
__device__ __forceinline__ int deferred_to(int blk, int r) {
    return (unsigned)(r - kDef0) < (unsigned)kFHeads ? (blk - kF * (r - kDef0)) & (kFHeads - 1) : kF;
}

__device__ __forceinline__ unsigned role_of_sm(unsigned smid) {
    const unsigned u = smid >> 1;
    const unsigned g = u < 32 ? u & 7 : u < 60 ? 1 + (u - 32) % 7 : u < 62 ? u - 54 : 0;
    const unsigned t = u < 32 ? u >> 3 : u < 60 ? 4 + (u - 32) / 7 : u < 62 ? 8 : u - 58;
    const unsigned lin = 16 * g + (g == 7 ? 2 : 0) + 2 * t + (smid & 1);
    return lin < 2 ? lin + kStream : lin < 48 ? lin - 2 : lin < 50 ? lin + (kStream + 2 - 48) : lin - 4;
}
static_assert(kGrid == 132 && kTeams == 4, "role_of_sm");
struct Scalars { const __nv_bfloat16* p[4]; };

__global__ void __launch_bounds__(kThreads, 1)
attn_kernel(const __grid_constant__ Scalars scal, const int* __restrict__ qk, int by_sm, const __nv_bfloat16* __restrict__ kcos,
            const __nv_bfloat16* __restrict__ ksin, const int* __restrict__ qv, const __nv_bfloat16* __restrict__ q,
            const __nv_bfloat16* __restrict__ qcos, const __nv_bfloat16* __restrict__ qsin,
            __nv_bfloat16* __restrict__ out, const __grid_constant__ CUtensorMap tmv) {
    extern __shared__ __align__(128) unsigned char smem[];
    const int warp = threadIdx.x >> 5, lane = threadIdx.x & 31;
    const uint32_t full0 = s2u(smem + kOffBar), empty0 = full0 + 2 * kNS * 8;
    const uint32_t sfull = empty0 + 2 * kNS * 8, sempty = sfull + 16, mxbar = sempty + 16, fine = mxbar + 16;
    volatile unsigned int* s_misc = reinterpret_cast<volatile unsigned int*>(smem + kOffMisc);
    uint64_t pol = 0;

    if (threadIdx.x == kCW * 32 && blockIdx.x < kStream)
        asm volatile("cp.async.bulk.prefetch.L2.global [%0], %1;"
                     ::"l"(scal.p[blockIdx.x & 3] + (blockIdx.x >> 2) * (kNH * kS * 4 / kStream)), "n"(kNH * kS * 4 / kStream * 2) : "memory");
    unsigned bid = blockIdx.x;
    if (by_sm) {
        unsigned smid, nsm;
        asm volatile("mov.u32 %0, %%smid;" : "=r"(smid));
        asm volatile("mov.u32 %0, %%nsmid;" : "=r"(nsm));
        if (nsm == kGrid) bid = role_of_sm(smid);
    }
    if (threadIdx.x == kCW * 32 && bid < kStream) {
        const int m = bid % kSlots;
        const uint32_t sm0 = s2u(smem);
        for (int i = 0; i < 2 * kNS; i++) mbar_init(full0 + 8 * i, 1);
        asm volatile("fence.mbarrier_init.release.cluster;" ::: "memory");
        asm volatile("createpolicy.fractional.L2::evict_first.b64 %0, 1.0;" : "=l"(pol));
        const int* k0 = qk + (size_t)(bid / kSlots * kS + m * kHRows) * kD;
#pragma unroll
        for (int h = 0; h < 2; h++) {
            mbar_expect(full0 + 16 + 8 * h, kHalf);
            bulk_g2s_stream(sm0 + kChunk + h * kHalf, k0 + h * (kS / 2 * kD), kHalf, full0 + 16 + 8 * h, pol);
        }
#pragma unroll
        for (int h = 0; h < 2; h++) {
            mbar_expect(full0 + 8 * h, kHalf);
            bulk_g2s(sm0 + h * kHalf, kcos + (h * (kS / 2) + m * kHRows) * kD, kHalf / 2, full0 + 8 * h);
            bulk_g2s(sm0 + h * kHalf + kHalf / 2, ksin + (h * (kS / 2) + m * kHRows) * kD, kHalf / 2, full0 + 8 * h);
        }
#pragma unroll
        for (int h = 0; h < 2; h++) {
            mbar_expect(full0 + 32 + 8 * h, kHalf);
            bulk_g2s_stream(sm0 + 2 * kChunk + h * kHalf, k0 + (kTeams * kS + h * (kS / 2)) * kD, kHalf, full0 + 32 + 8 * h, pol);
        }
    }

    if (bid >= kStream) {
        const int team = bid - kStream;
        if (threadIdx.x == 0) s_misc[0] = ld_relaxed(&g_epoch);
        __syncthreads();
        if (threadIdx.x == 0 && atomicAdd(&g_arrive, 1u) == kGrid - 1) { g_arrive = 0u; g_epoch = s_misc[0] + 1u; }
        if (warp >= 3 * kMG) return;
        const int grp = warp / 3, t = threadIdx.x - grp * 96;
        constexpr int kRecBytes = kSlots * kRecWords * 8;
        if (t == 0) {
            mbar_init(s2u(smem + kOffBar) + grp * 8, 1);
            asm volatile("fence.mbarrier_init.release.cluster;" ::: "memory");
        }
        asm volatile("bar.sync %0, 96;" ::"r"(3 + grp) : "memory");
        for (int r = grp; r < kRounds; r += kMG) {
            const int g = r % kMG;
            const int tt = threadIdx.x - g * 96, qd = tt % 48, half = tt / 48;
            const uint32_t tag = round_tag(s_misc[0], r);
            const uint32_t tlo = tag & 15u, thi = tag >> 4;
            const unsigned long long* rec = g_rec + ((size_t)(r % kPR) * kStream + team * kSlots) * kRecWords;
            unsigned long long ml, x[16], y[16];
            {
                const unsigned long long* buf = reinterpret_cast<const unsigned long long*>(smem + g * kRecBytes);
                const uint32_t mb = s2u(smem + kOffBar) + g * 8;
                if (tt < 32) {
                    const int want = r == kRounds - 1 ? kQuick : kSlots;
                    for (int i2 = 0;; i2++) {
                        ml = ld_rec1(rec + lane * kRecWords + 96);
                        if (__popc(__ballot_sync(0xffffffffu, ml_bad(ml, tag) == 0)) >= want) break;
                        if (i2 > kSpin) __trap();
                        __nanosleep(kSleep);
                    }
                    if (tt == 0) {
                        mbar_expect(mb, kRecBytes);
                        bulk_g2s(s2u(buf), rec, kRecBytes, mb);
                    }
                }
                mbar_wait(mb, (r / kMG) & 1);
                ml = buf[lane * kRecWords + 96];
#pragma unroll
                for (int i = 0; i < 16; i++) {
                    const ulonglong2 u = *reinterpret_cast<const ulonglong2*>(buf + (half * 16 + i) * kRecWords + 2 * qd);
                    x[i] = u.x; y[i] = u.y;
                }
                const unsigned long long* po = rec + half * 16 * kRecWords + 2 * qd;
                for (int it = 0;; it++) {
                    uint32_t any = ml_bad(ml, tag);
                    if (any) ml = ld_rec1(rec + lane * kRecWords + 96);
#pragma unroll
                    for (int i = 0; i < 16; i++) {
                        const uint32_t bad = rec_bad(x[i], tlo, thi) | rec_bad(y[i], tlo, thi);
                        if (bad) ld_rec2(po + i * kRecWords, x[i], y[i]);
                        any |= bad;
                    }
                    if (__all_sync(0xffffffffu, any == 0)) break;
                    if (it > kSpin) __trap();
                }
            }
            const float M = ml_m(ml);
            const float MM = warp_max(M);
            const float w = exp2f(M - MM);
            float LL = w * ml_l(ml);
#pragma unroll
            for (int o = 16; o > 0; o >>= 1) LL += __shfl_xor_sync(0xffffffffu, LL, o);
            float4 a = make_float4(0.f, 0.f, 0.f, 0.f);
#pragma unroll
            for (int i = 0; i < 16; i++) {
                const float wi = __shfl_sync(0xffffffffu, w, half * 16 + i);
                a.x = fmaf(wi, rec_lo(x[i]), a.x);
                a.y = fmaf(wi, rec_hi(x[i]), a.y);
                a.z = fmaf(wi, rec_lo(y[i]), a.z);
                a.w = fmaf(wi, rec_hi(y[i]), a.w);
            }
            float* rb = reinterpret_cast<float*>(smem + kMG * kRecBytes) + (2 * g + ((r / kMG) & 1)) * kD + 4 * qd;
            if (half == 1) *reinterpret_cast<float4*>(rb) = a;
            asm volatile("bar.sync %0, 96;" ::"r"(3 + g) : "memory");
            if (half == 0) {
                const float4 u = *reinterpret_cast<float4*>(rb);
                if ((unsigned)(r - kDef0) < (unsigned)kFHeads) {
                    unsigned long long* pre = g_pre + (size_t)(team * kFHeads + r - kDef0) * kRecWords;
                    const uint32_t ptag = s_misc[0] % 255u + 1u;
                    st_rec(pre + 2 * qd, a.x + u.x, a.y + u.y, ptag);
                    st_rec(pre + 2 * qd + 1, a.z + u.z, a.w + u.w, ptag);
                    if (qd == 0) st_ml(pre + 96, MM, LL, ptag);
                } else {
                    const float inv = __fdividef(1.0f, LL);
                    const __nv_bfloat162 o0 = __floats2bfloat162_rn((a.x + u.x) * inv, (a.y + u.y) * inv);
                    const __nv_bfloat162 o1 = __floats2bfloat162_rn((a.z + u.z) * inv, (a.w + u.w) * inv);
                    uint2 ov;
                    ov.x = *reinterpret_cast<const uint32_t*>(&o0);
                    ov.y = *reinterpret_cast<const uint32_t*>(&o1);
                    *reinterpret_cast<uint2*>(out + (size_t)(kTeams * r + team) * kD + 4 * qd) = ov;
                }
            }
            if (tt == 95)
                asm volatile("st.relaxed.gpu.global.u32 [%0], %1;" ::"l"(&g_mdone[(team * kMG + g) * 32]), "r"(s_misc[0] * kRounds + r + 1) : "memory");
        }
        return;
    }

    const int m = bid % kSlots, team = bid / kSlots;
    const int row0 = m * kHRows;

    if (warp == kCW) {
        unsigned int epoch = 0;
        const size_t off0 = ((size_t)team * kS + row0) * kD;
        const uint32_t sm0 = s2u(smem);
        if (lane == 0) {
            epoch = ld_relaxed(&g_epoch);
            s_misc[0] = epoch;
            s_misc[1] = 0;
            for (int j = 0; j < kNP; j++) {
                s_misc[4 + 2 * j] = epoch * (kStream * (4 * kRounds - 2));
                s_misc[5 + 2 * j] = clock32();
            }
        }
        __syncwarp();
        asm volatile("bar.sync 2, %0;" ::"n"(kThreads) : "memory");
        if (lane == 0) {
            unsigned int cum = epoch * (kStream * (4 * kRounds - 2)) + 4 * kStream;
            int use0 = kNS, use1 = kNS;
            const int* kp = qk + off0;
            const int* vp = qv + off0;
            for (int ph2 = 4; ph2 < 2 * (2 * kRounds + kF); ph2++) {
                const int p = ph2 >> 1, h = ph2 & 1;
                const bool isv = (p & 1) == 0 || p == 2 * kRounds - 1;
                const int r = p == 2 * kRounds - 1 ? kRounds - 1 : isv ? (p >> 1) - 1 : (p + 1) >> 1;
                const uint32_t dm = (isv && (unsigned)(r - kDef0) < (unsigned)kFHeads)
                                        ? ((((1u << kF) - 1) * 0x101u << ((kF * (r - kDef0)) & (kFHeads - 1))) >> (8 + 4 * h)) & 15u : 0u;
                const unsigned int need = cum - max(kRampEnd - ph2, 0) * kRampStep -
                    ((unsigned)(ph2 - (4 * kDef0 + 4)) < (unsigned)(4 * kFHeads + 2) ? kLeadDef : kLead);
                cum += kStream - (kStream / 4) * __popc(dm);
                const bool skip = (dm >> (m / 8)) & 1;
                const int u = h ? use1 : use0;
                const int slot = u >= kNS ? u - kNS : u;
                const uint32_t dst = sm0 + slot * kChunk + h * kHalf, fullb = full0 + 16 * slot + 8 * h;
                const int* src = (isv ? vp : kp) + (size_t)(r * kTeams * kS + h * (kS / 2)) * kD;
                if (!skip) {
                    const int un = u + 1 == 2 * kNS ? 0 : u + 1;
                    if (h) use1 = un; else use0 = un;
                    mbar_wait(fullb + 2 * kNS * 8, u >= kNS ? 0 : 1);
                    if (p < 2 * kRounds) mbar_expect(fullb, kHalf);
                }
                asm volatile("" ::"l"(src), "r"(dst) : "memory");
                if (!skip)
                    for (int it = 0;; it++) {
                        uint32_t x, tx, y, ty;
                        asm volatile("ld.volatile.shared.v4.u32 {%0, %1, %2, %3}, [%4];"
                                     : "=r"(x), "=r"(tx), "=r"(y), "=r"(ty) : "r"(sm0 + kOffMisc + 16) : "memory");
                        const uint32_t now = clock32();
                        x += min(((now - tx) * kRate) >> 10, kAhead);
                        y += min(((now - ty) * kRate) >> 10, kAhead);
                        if ((int)((x - need) & (y - need)) >= 0) break;
                        if (it > 16 * kSpin) __trap();
                    }
                if (ph2 == 2 * (2 * kRounds + kF) - 1) s_misc[1] = 1;
                if (p >= 2 * kRounds || skip) {
                    const int hi = m / kFG;
                    const int row = (kTeams * (kDef0 + hi) + team) * kS + ((kF * hi + p - 2 * kRounds) & (kFHeads - 1)) * kFRows + h * (kFRows / 2);
                    const uint32_t fb = fine + 8 * (kFBoxes / 2) * (ph2 - 4 * kRounds);
#pragma unroll 1
                    for (int w = 0; w < kFBoxes / 2; w++)
                        asm volatile("{\n.reg .pred p;\nsetp.ne.u32 p, %6, 0;\n"
                                     "@p cp.async.bulk.tensor.2d.shared::cluster.global.tile.mbarrier::complete_tx::bytes.L2::cache_hint [%0], [%1, {%2, %3}], [%4], %5;\n}"
                                     ::"r"(dst + w * (kChunk / kFBoxes)), "l"(&tmv), "r"((m % kFG) * kFW), "r"(row + w * (kFRows / kFBoxes)),
                                       "r"(fb + 8 * w), "l"(pol), "r"((uint32_t)!skip) : "memory");
                } else {
                    bulk_g2s_stream(dst, src, kHalf, fullb, pol);
                }
            }
        }
    } else if (warp >= kCW + 2) {
        asm volatile("bar.sync 2, %0;" ::"n"(kThreads) : "memory");
        if (lane == 0) {
            const int j = warp - (kCW + 2);
            for (int it = 0; !s_misc[1]; it++) {
                const uint32_t t = clock32();
                const uint32_t v = ld_relaxed(g_prog + j * 1024);
                asm volatile("st.volatile.shared.v2.u32 [%0], {%1, %2};" ::"r"(s2u(smem) + kOffMisc + 16 + 8 * j), "r"(v), "r"(t) : "memory");
                if (s_misc[1]) break;
                if (it > kSpin) __trap();
                __nanosleep(kPollSleep);
            }
        }
    } else if (warp == kCW + 1) {
        {
            if (lane < 2 * kNS + 6) mbar_init(empty0 + 8 * lane, lane < 2 * kNS ? kCW / 2 : (lane >= 2 * kNS + 2 && lane < 2 * kNS + 4) ? 1 : kCW);
            asm volatile("fence.mbarrier_init.release.cluster;" ::: "memory");
        }
        asm volatile("bar.sync 2, %0;" ::"n"(kThreads) : "memory");
        const unsigned int epoch = s_misc[0];
        if (lane == 0 && atomicAdd(&g_arrive, 1u) == kGrid - 1) { g_arrive = 0u; g_epoch = epoch + 1u; }
        {
            const uint32_t sm0 = s2u(smem);
            const __nv_bfloat16* src = scal.p[lane >> 3] + (size_t)team * kS + row0 + (lane & 4) * (kS / 8) + (lane & 3) * 8;
            const __nv_bfloat16* qs = q + team * kD + lane * 8;
#pragma unroll 1
            for (int r = kEarly; r < kRounds; r++) {
                cp16(sm0 + kOffScal + r * 512 + lane * 16, src + (size_t)r * (kTeams * kS));
                if (lane < 24) cp16(sm0 + kOffQ + r * (kD * 2) + lane * 16, qs + r * (kTeams * kD));
                if (r == 2 * kEarly - 1 || r == kRounds - 1) asm volatile("cp.async.commit_group;" ::: "memory");
            }
        }
        uint32_t cs[2][4];
#pragma unroll
        for (int i = 0; i < 2; i++) {
            const int p = (lane + 32 * i) % 48;
            cs[i][0] = ld_pair(qcos + 2 * p); cs[i][1] = ld_pair(qcos + 2 * p + 96);
            cs[i][2] = ld_pair(qsin + 2 * p); cs[i][3] = ld_pair(qsin + 2 * p + 96);
        }
        asm volatile("cp.async.wait_group 1;" ::: "memory");
        __syncwarp();
        for (int r = 0; r < kRounds; r++) {
            const float* sc = reinterpret_cast<const float*>(smem + kOffSc) + (r & 1) * (kCW * kScStride);
            const uint32_t tag = round_tag(epoch, r);
            unsigned long long* rec = g_rec + ((size_t)(r % kPR) * kStream + team * kSlots + m) * kRecWords;
            if (r >= kEarly && r < kEarly + kF * kFBoxes && lane == 0) {
                mbar_init(fine + 8 * (r - kEarly), 1);
                asm volatile("fence.mbarrier_init.release.cluster;" ::: "memory");
                mbar_expect(fine + 8 * (r - kEarly), kChunk / kFBoxes);
                asm volatile("fence.proxy.async.shared::cta;" ::: "memory");
            }
            if (r == kPrep + m / 2) {
                const unsigned long long* pre = g_pre + (size_t)(team * kFHeads + m / kFG) * kRecWords;
                const unsigned long long* lgp = g_lg + (size_t)(team * kFHeads + m / kFG) * (kF * kFRows);
                const uint32_t ptag = epoch % 255u + 1u;
                unsigned long long ml, po;
                for (int it = 0;; it++) {
                    ml = ld_rec1(pre + 96);
                    po = ld_rec1(pre + (m % kFG) * (kFW / 2) + lane % (kFW / 2));
                    if (!(ml_bad(ml, ptag) | rec_bad(po, ptag & 15u, ptag >> 4))) break;
                    if (it > kSpin) __trap();
                }
                const float inv = 1.0f / ml_l(ml);
                if (lane < kFW / 2) {
                    reinterpret_cast<float*>(smem + kOffFin)[lane] = rec_lo(po) * inv;
                    reinterpret_cast<float*>(smem + kOffFin)[kFW / 2 + lane] = rec_hi(po) * inv;
                }
#pragma unroll 1
                for (int c = 0; c < kF; c++) {
                    unsigned long long u[8];
                    for (int it = 0;; it++) {
                        uint32_t bad = 0;
#pragma unroll
                        for (int k = 0; k < 8; k++) {
                            u[k] = ld_rec1(lgp + c * kFRows + 32 * k + lane);
                            bad |= ml_bad(u[k], ptag);
                        }
                        if (!bad) break;
                        if (it > kSpin) __trap();
                    }
#pragma unroll
                    for (int k = 0; k < 8; k++)
                        reinterpret_cast<float*>(smem + kOffW)[c * kFRows + 32 * k + lane] = ml_l(u[k]) * exp2f(ml_m(u[k]) - ml_m(ml)) * inv;
                }
                __syncwarp();
            }
            if (r == kRounds - 3 && lane == 0) asm volatile("prefetch.tensormap [%0];" ::"l"(&tmv) : "memory");
            if (r == kEarly) {
                asm volatile("cp.async.wait_all;" ::: "memory");
                __syncwarp();
            }
            if (r + kEarly < kRounds) {
                uint32_t* qrow = reinterpret_cast<uint32_t*>(smem + kOffQ + (r + kEarly) * (kD * 2));
                rotate_q(qrow, lane, cs[0][0], cs[0][1], cs[0][2], cs[0][3]);
                if (lane < 16) rotate_q(qrow, lane + 32, cs[1][0], cs[1][1], cs[1][2], cs[1][3]);
            }
            if (r >= kPR) {
                const unsigned int* mdone = &g_mdone[(team * kMG + r % kMG) * 32];
                const unsigned int need = epoch * kRounds + r - kPR + 1;
                for (int it = 0; (int)(ld_relaxed(mdone) - need) < 0; it++)
                    if (it > kSpin) __trap();
            }
            mbar_wait(sfull + 8 * (r & 1), (r >> 1) & 1);
            const float M = sc[0];
            float L = lane < kCW ? sc[lane * kScStride + 1] : 0.f;
            float acc[2][6];
#pragma unroll
            for (int ww = 0; ww < kCW; ww++) {
#pragma unroll
                for (int j = 0; j < 3; j++) {
                    const float2 t = *reinterpret_cast<const float2*>(sc + ww * kScStride + 4 + 64 * j + 2 * lane);
                    acc[ww & 1][2 * j] = ww < 2 ? t.x : acc[ww & 1][2 * j] + t.x;
                    acc[ww & 1][2 * j + 1] = ww < 2 ? t.y : acc[ww & 1][2 * j + 1] + t.y;
                }
                if ((ww & 3) == 3 && ww < 15) L += __shfl_xor_sync(0xffffffffu, L, 8 >> (ww >> 2));
            }
            L += __shfl_xor_sync(0xffffffffu, L, 1);
#pragma unroll
            for (int j = 0; j < 3; j++)
                st_rec(rec + 32 * j + lane, acc[0][2 * j] + acc[1][2 * j], acc[0][2 * j + 1] + acc[1][2 * j + 1], tag);
            if (lane == 0) st_ml(rec + 96, M, L, tag);
            __syncwarp();
            if (lane == 0) mbar_arrive(sempty + 8 * (r & 1));
        }
    } else {
        int dp[3];
#pragma unroll
        for (int j = 0; j < 3; j++) dp[j] = (64 * j + 2 * lane + 96) % kD;
        {
            const uint32_t sm0 = s2u(smem);
            if (warp < kEarly) {
                cp16(sm0 + kOffScal + threadIdx.x * 16, scal.p[lane >> 3] + (size_t)(kTeams * warp + team) * kS + row0 + (lane & 4) * (kS / 8) + (lane & 3) * 8);
            } else if (warp < 2 * kEarly && lane < 24) {
                cp16(sm0 + kOffQ + (warp - kEarly) * (kD * 2) + lane * 16, q + (size_t)(kTeams * (warp - kEarly) + team) * kD + lane * 8);
            }
            asm volatile("cp.async.commit_group;" ::: "memory");
        }
        const int p = threadIdx.x % 48, g = threadIdx.x / 48;
        const uint32_t c_lo = ld_pair(qcos + 2 * p), c_hi = ld_pair(qcos + 2 * p + 96);
        const uint32_t s_lo = ld_pair(qsin + 2 * p), s_hi = ld_pair(qsin + 2 * p + 96);
        float kc[kR][6], ks[kR][6];
        asm volatile("bar.sync 2, %0;" ::"n"(kThreads) : "memory");
        const int half = warp / (kCW / 2);
        const uint32_t fullh = full0 + 8 * half, emptyh = empty0 + 8 * half;
        mbar_wait(fullh, 0);
#pragma unroll
        for (int i = 0; i < kR; i++) {
            const unsigned char* cb = smem + half * (kHalf / 2) + (warp * kR + i) * (kD * 2);
#pragma unroll
            for (int j = 0; j < 3; j++) {
                const uint32_t uc = *reinterpret_cast<const uint32_t*>(cb + 128 * j + 4 * lane);
                const uint32_t us = *reinterpret_cast<const uint32_t*>(cb + kHalf / 2 + 2 * dp[j]);
                kc[i][2 * j] = bf_lo(uc); kc[i][2 * j + 1] = bf_hi(uc);
                const float sg = (j == 0 || (j == 1 && lane < 16)) ? 1.f : -1.f;
                ks[i][2 * j] = sg * bf_lo(us); ks[i][2 * j + 1] = sg * bf_hi(us);
            }
        }
        __syncwarp();
        if (lane == 0) mbar_arrive(emptyh);
        asm volatile("cp.async.wait_group 0;" ::: "memory");
        asm volatile("bar.sync 1, %0;" ::"n"(kCW * 32) : "memory");
        if (g < kEarly) rotate_q(reinterpret_cast<uint32_t*>(smem + kOffQ + g * (kD * 2)), p, c_lo, c_hi, s_lo, s_hi);
        asm volatile("bar.sync 1, %0;" ::"n"(kCW * 32) : "memory");
        const float scale_log2e = 1.4426950408889634f * rsqrtf((float)kD);
        float* my0 = reinterpret_cast<float*>(smem + kOffSc) + warp * kScStride;

        float* s_max = reinterpret_cast<float*>(smem + kOffMax);
        int slot = 1;
        uint32_t ph = 0;
        float lgc[kR] = {0.f, 0.f, 0.f, 0.f};
        for (int it = 0; it <= kRounds; it++) {
            float lg[kR];
            if (it < kRounds) {
                float qa[6], qb[6];
#pragma unroll
                for (int j = 0; j < 3; j++) {
                    const uint32_t qo = *reinterpret_cast<const uint32_t*>(smem + kOffQ + it * (kD * 2) + 2 * (64 * j + 2 * lane));
                    const uint32_t qp = *reinterpret_cast<const uint32_t*>(smem + kOffQ + it * (kD * 2) + 2 * dp[j]);
                    qa[2 * j] = bf_lo(qo); qa[2 * j + 1] = bf_hi(qo);
                    qb[2 * j] = bf_lo(qp); qb[2 * j + 1] = bf_hi(qp);
                }
                const unsigned char* sp = smem + kOffScal + it * (4 * kRows * 2) + warp * (kR * 2);
                const uint2 uks = *reinterpret_cast<const uint2*>(sp);
                const uint2 ukz = *reinterpret_cast<const uint2*>(sp + kRows * 2);
                const float kz[4] = {bf_lo(ukz.x), bf_hi(ukz.x), bf_lo(ukz.y), bf_hi(ukz.y)};
                const float sk[4] = {bf_lo(uks.x), bf_hi(uks.x), bf_lo(uks.y), bf_hi(uks.y)};
                mbar_wait(fullh + 16 * slot, ph);
                if ((threadIdx.x & 255) < kNP) asm volatile("red.relaxed.gpu.global.add.u32 [%0], 1;" ::"l"(g_prog + lane * 1024) : "memory");
                const unsigned char* kb = smem + slot * kChunk + warp * (kR * kRowBytes) + lane * 8;
#pragma unroll
                for (int i = 0; i < kR; i++) {
                    float dot = 0.f;
#pragma unroll
                    for (int j = 0; j < 3; j++) {
                        const int2 kk = *reinterpret_cast<const int2*>(kb + i * kRowBytes + 256 * j);
                        const float e0 = qa[2 * j] * kc[i][2 * j] + qb[2 * j] * ks[i][2 * j];
                        const float e1 = qa[2 * j + 1] * kc[i][2 * j + 1] + qb[2 * j + 1] * ks[i][2 * j + 1];
                        dot = fmaf((float)kk.x - kz[i], e0, dot);
                        dot = fmaf((float)kk.y - kz[i], e1, dot);
                    }
                    lg[i] = dot;
                }
                __syncwarp();
                if (lane == 0) mbar_arrive(emptyh + 16 * slot);
                if (++slot == kNS) { slot = 0; ph ^= 1; }
#pragma unroll
                for (int o = 16; o > 0; o >>= 1) {
#pragma unroll
                    for (int i = 0; i < kR; i++) lg[i] += __shfl_xor_sync(0xffffffffu, lg[i], o);
                }
                float mw = -INFINITY;
#pragma unroll
                for (int i = 0; i < kR; i++) {
                    lg[i] = lg[i] * sk[i] * scale_log2e;
                    mw = fmaxf(mw, lg[i]);
                }
                if (lane == 0) {
                    s_max[(it & 3) * kCW + warp] = mw;
                    mbar_arrive(mxbar + 8 * (it & 1));
                }
            }
            if (it > 0) {
                const int r = it - 1;
                float* my = my0 + (r & 1) * (kCW * kScStride);
                const int df = deferred_to(4 * half + m / 8, r);
                const unsigned char* sp = smem + kOffScal + r * (4 * kRows * 2) + warp * (kR * 2);
                const uint2 uvs = *reinterpret_cast<const uint2*>(sp + 2 * kRows * 2);
                const uint2 uvz = *reinterpret_cast<const uint2*>(sp + 3 * kRows * 2);
                const float vz[4] = {bf_lo(uvz.x), bf_hi(uvz.x), bf_lo(uvz.y), bf_hi(uvz.y)};
                const float sv[4] = {bf_lo(uvs.x), bf_hi(uvs.x), bf_lo(uvs.y), bf_hi(uvs.y)};
                mbar_wait(mxbar + 8 * (r & 1), (r >> 1) & 1);
                float M;
                {
                    const float4* pm4 = reinterpret_cast<const float4*>(s_max + (r & 3) * kCW);
                    const float4 m0 = pm4[0], m1 = pm4[1], m2 = pm4[2], m3 = pm4[3];
                    M = fmaxf(fmaxf(fmaxf(fmaxf(m0.x, m0.y), fmaxf(m0.z, m0.w)), fmaxf(fmaxf(m1.x, m1.y), fmaxf(m1.z, m1.w))),
                              fmaxf(fmaxf(fmaxf(m2.x, m2.y), fmaxf(m2.z, m2.w)), fmaxf(fmaxf(m3.x, m3.y), fmaxf(m3.z, m3.w))));
                }
                float lw = 0.f, cz = 0.f, pv[kR];
#pragma unroll
                for (int i = 0; i < kR; i++) {
                    const float p = exp2f(lgc[i] - M);
                    lw += p;
                    pv[i] = p * sv[i];
                    cz = fmaf(pv[i], vz[i], cz);
                }
                mbar_wait(sempty + 8 * (r & 1), ((r >> 1) & 1) ^ 1);
                if (lane == 0) { my[0] = M; my[1] = lw; }
                float acc[6] = {-cz, -cz, -cz, -cz, -cz, -cz};
                if (df < kF) {
                    if (lane < kR)
                        st_ml(g_lg + ((team * kFHeads + r - kDef0) * kF + df) * kFRows + (m % 8) * kHRows + (warp % 8) * kR + lane, M,
                              lane == 0 ? pv[0] : lane == 1 ? pv[1] : lane == 2 ? pv[2] : pv[3], s_misc[0] % 255u + 1u);
                } else {
                    mbar_wait(fullh + 16 * slot, ph);
                    if ((threadIdx.x & 255) < kNP) asm volatile("red.relaxed.gpu.global.add.u32 [%0], 1;" ::"l"(g_prog + lane * 1024) : "memory");
                    const unsigned char* vb = smem + slot * kChunk + warp * (kR * kRowBytes) + lane * 8;
#pragma unroll
                    for (int i = 0; i < kR; i++) {
#pragma unroll
                        for (int j = 0; j < 3; j++) {
                            const int2 vv = *reinterpret_cast<const int2*>(vb + i * kRowBytes + 256 * j);
                            acc[2 * j] = fmaf(pv[i], (float)vv.x, acc[2 * j]);
                            acc[2 * j + 1] = fmaf(pv[i], (float)vv.y, acc[2 * j + 1]);
                        }
                    }
                    __syncwarp();
                    if (lane == 0) mbar_arrive(emptyh + 16 * slot);
                    if (++slot == kNS) { slot = 0; ph ^= 1; }
                }
#pragma unroll
                for (int j = 0; j < 3; j++)
                    *reinterpret_cast<float2*>(my + 4 + 64 * j + 2 * lane) = make_float2(acc[2 * j], acc[2 * j + 1]);
                __syncwarp();
                if (lane == 0) mbar_arrive(sfull + 8 * (r & 1));
            }
#pragma unroll
            for (int i = 0; i < kR; i++) lgc[i] = lg[i];
        }
        {
            const int cp = lane < kFW / 2 ? lane : 0;
            const int ft = threadIdx.x < kFW ? threadIdx.x : 0;
            const float fin = reinterpret_cast<const float*>(smem + kOffFin)[ft];
            __nv_bfloat16* op = out + (size_t)(kTeams * (kDef0 + m / kFG) + team) * kD + (m % kFG) * kFW + 2 * (ft % (kFW / 2)) + ft / (kFW / 2);
            float a0 = 0.f, a1 = 0.f, b0 = 0.f, b1 = 0.f;
#pragma unroll 1
            for (int f = 0; f < kF; f++) {
                const float* sw = reinterpret_cast<const float*>(smem + kOffW) + f * kFRows + (warp >> 2) * 16 + (warp & 3) * 4;
                const unsigned char* vb = smem + slot * kChunk + ((warp >> 2) * 16 + (warp & 3) * 4) * (kFW * 4) + cp * 8;
                const uint32_t fb = fine + (f * kFBoxes + (warp >> 2)) * 8;
                float* part = reinterpret_cast<float*>(smem + kOffPart) + f * (kFW * kPartStride);
                float4 w[4];
#pragma unroll
                for (int k = 0; k < 4; k++) w[k] = *reinterpret_cast<const float4*>(sw + 64 * k);
#pragma unroll
                for (int k = 0; k < 4; k++) {
                    mbar_wait(fb + 32 * k, 0);
                    if ((k & 1) && warp == kCW - 1 && lane < kNP && f < kF - 1) asm volatile("red.relaxed.gpu.global.add.u32 [%0], 1;" ::"l"(g_prog + lane * 1024) : "memory");
                    const int2 v0 = *reinterpret_cast<const int2*>(vb + k * (64 * kFW * 4));
                    const int2 v1 = *reinterpret_cast<const int2*>(vb + k * (64 * kFW * 4) + kFW * 4);
                    const int2 v2 = *reinterpret_cast<const int2*>(vb + k * (64 * kFW * 4) + 2 * kFW * 4);
                    const int2 v3 = *reinterpret_cast<const int2*>(vb + k * (64 * kFW * 4) + 3 * kFW * 4);
                    a0 = fmaf(w[k].x, (float)v0.x, a0); a1 = fmaf(w[k].x, (float)v0.y, a1);
                    b0 = fmaf(w[k].y, (float)v1.x, b0); b1 = fmaf(w[k].y, (float)v1.y, b1);
                    a0 = fmaf(w[k].z, (float)v2.x, a0); a1 = fmaf(w[k].z, (float)v2.y, a1);
                    b0 = fmaf(w[k].w, (float)v3.x, b0); b1 = fmaf(w[k].w, (float)v3.y, b1);
                }
                if (lane < kFW / 2) {
                    part[lane * kPartStride + warp] = a0 + b0;
                    part[(kFW / 2 + lane) * kPartStride + warp] = a1 + b1;
                }
                if (warp >= 2) {
                    asm volatile("bar.arrive %0, %1;" ::"r"(3 + f), "n"(kCW * 32) : "memory");
                } else {
                    asm volatile("bar.sync %0, %1;" ::"r"(3 + f), "n"(kCW * 32) : "memory");
                    const float4* ps = reinterpret_cast<const float4*>(part + ft * kPartStride);
                    const float4 p0 = ps[0], p1 = ps[1], p2 = ps[2], p3 = ps[3];
                    const float sum = (((p0.x + p0.y) + (p0.z + p0.w)) + ((p1.x + p1.y) + (p1.z + p1.w))) +
                                      (((p2.x + p2.y) + (p2.z + p2.w)) + ((p3.x + p3.y) + ((p3.z + p3.w) + fin)));
                    asm volatile("{\n.reg .pred p;\n.reg .b16 h;\nsetp.ne.u32 p, %2, 0;\ncvt.rn.bf16.f32 h, %1;\n@p st.global.b16 [%0], h;\n}"
                                 ::"l"(op), "f"(sum), "r"((uint32_t)(f == kF - 1 && threadIdx.x < kFW)) : "memory");
                }
                if (++slot == kNS) slot = 0;
            }
        }
    }
}

__global__ void __launch_bounds__(256)
attn_fallback(const __nv_bfloat16* __restrict__ q, const int* __restrict__ qk,
              const __nv_bfloat16* __restrict__ ksc, const __nv_bfloat16* __restrict__ kzp,
              const int* __restrict__ qv, const __nv_bfloat16* __restrict__ vsc,
              const __nv_bfloat16* __restrict__ vzp, const __nv_bfloat16* __restrict__ qcos,
              const __nv_bfloat16* __restrict__ qsin, const __nv_bfloat16* __restrict__ kcos,
              const __nv_bfloat16* __restrict__ ksin, __nv_bfloat16* __restrict__ out) {
    __shared__ float qr[kD], lg[kS], red[8];
    const int h = blockIdx.x, t = threadIdx.x, warp = t >> 5, lane = t & 31;
    if (t < kD) {
        const float x = __bfloat162float(q[h * kD + t]);
        const float y = t < kD / 2 ? -__bfloat162float(q[h * kD + t + kD / 2]) : __bfloat162float(q[h * kD + t - kD / 2]);
        qr[t] = bf_round(bf_round(x * __bfloat162float(qcos[t])) + bf_round(y * __bfloat162float(qsin[t])));
    }
    __syncthreads();
    const float scale_log2e = 1.4426950408889634f * rsqrtf((float)kD);
    float mw = -INFINITY;
    for (int s = warp; s < kS; s += 8) {
        const size_t row = (size_t)h * kS + s;
        const float z = __bfloat162float(kzp[row]);
        float dot = 0.f;
        for (int d = lane; d < kD; d += 32) {
            const int dp = d < kD / 2 ? d + kD / 2 : d - kD / 2;
            const float sn = __bfloat162float(ksin[s * kD + dp]);
            const float e = qr[d] * __bfloat162float(kcos[s * kD + d]) + qr[dp] * (d < kD / 2 ? sn : -sn);
            dot = fmaf((float)qk[row * kD + d] - z, e, dot);
        }
        for (int o = 16; o > 0; o >>= 1) dot += __shfl_xor_sync(0xffffffffu, dot, o);
        dot = dot * __bfloat162float(ksc[row]) * scale_log2e;
        if (lane == 0) lg[s] = dot;
        mw = fmaxf(mw, dot);
    }
    if (lane == 0) red[warp] = mw;
    __syncthreads();
    float M = red[0];
    for (int i = 1; i < 8; i++) M = fmaxf(M, red[i]);
    __syncthreads();
    float l = 0.f;
    for (int s = t; s < kS; s += 256) { const float p = exp2f(lg[s] - M); l += p; lg[s] = p; }
    for (int o = 16; o > 0; o >>= 1) l += __shfl_xor_sync(0xffffffffu, l, o);
    if (lane == 0) red[warp] = l;
    __syncthreads();
    float L = 0.f;
    for (int i = 0; i < 8; i++) L += red[i];
    if (t < kD) {
        float acc = 0.f;
        for (int s = 0; s < kS; s++) {
            const size_t row = (size_t)h * kS + s;
            acc = fmaf(lg[s] * __bfloat162float(vsc[row]), (float)qv[row * kD + t] - __bfloat162float(vzp[row]), acc);
        }
        out[h * kD + t] = __float2bfloat16_rn(acc / L);
    }
}

}

extern "C" void kernel_launch(void* const* d_in, const int* in_sizes, int n_in, void* d_out, int out_size) {
    const __nv_bfloat16* q = (const __nv_bfloat16*)d_in[0];
    const int* qk = (const int*)d_in[1];
    const __nv_bfloat16* ksc = (const __nv_bfloat16*)d_in[2];
    const __nv_bfloat16* kzp = (const __nv_bfloat16*)d_in[3];
    const int* qv = (const int*)d_in[4];
    const __nv_bfloat16* vsc = (const __nv_bfloat16*)d_in[5];
    const __nv_bfloat16* vzp = (const __nv_bfloat16*)d_in[6];
    const __nv_bfloat16* qcos = (const __nv_bfloat16*)d_in[7];
    const __nv_bfloat16* qsin = (const __nv_bfloat16*)d_in[8];
    const __nv_bfloat16* kcos = (const __nv_bfloat16*)d_in[9];
    const __nv_bfloat16* ksin = (const __nv_bfloat16*)d_in[10];

    typedef CUresult (*EncodeFn)(CUtensorMap*, CUtensorMapDataType, cuuint32_t, void*, const cuuint64_t*, const cuuint64_t*,
                                 const cuuint32_t*, const cuuint32_t*, CUtensorMapInterleave, CUtensorMapSwizzle,
                                 CUtensorMapL2promotion, CUtensorMapFloatOOBfill);
    static EncodeFn encode = nullptr;
    static int by_sm = 0;
    static int mode = 0;
    if (!mode) {
        int dev = 0, sms = 0, occ = 0;
        cudaGetDevice(&dev);
        cudaDeviceGetAttribute(&sms, cudaDevAttrMultiProcessorCount, dev);
        cudaError_t e = cudaFuncSetAttribute(attn_kernel, cudaFuncAttributeMaxDynamicSharedMemorySize, kSmemBytes);
        if (e == cudaSuccess) e = cudaOccupancyMaxActiveBlocksPerMultiprocessor(&occ, attn_kernel, kThreads, kSmemBytes);
        void* fn = nullptr;
        cudaDriverEntryPointQueryResult qr;
        if (e == cudaSuccess) e = cudaGetDriverEntryPoint("cuTensorMapEncodeTiled", &fn, cudaEnableDefault, &qr);
        encode = (EncodeFn)fn;
        mode = (e == cudaSuccess && fn && occ * sms >= kGrid) ? 1 : 2;
        (void)cudaGetLastError();
        by_sm = sms == kGrid && occ == 1;
    }
    CUtensorMap tmv;
    bool fast = mode == 1;
    if (fast) {
        const cuuint64_t dims[2] = {(cuuint64_t)kD, (cuuint64_t)kNH * kS}, strides[1] = {(cuuint64_t)kRowBytes};
        const cuuint32_t box[2] = {(cuuint32_t)kFW, (cuuint32_t)(kFRows / kFBoxes)}, es[2] = {1, 1};
        fast = encode(&tmv, CU_TENSOR_MAP_DATA_TYPE_INT32, 2, (void*)qv, dims, strides, box, es, CU_TENSOR_MAP_INTERLEAVE_NONE,
                      CU_TENSOR_MAP_SWIZZLE_NONE, CU_TENSOR_MAP_L2_PROMOTION_L2_128B, CU_TENSOR_MAP_FLOAT_OOB_FILL_NONE) == CUDA_SUCCESS;
    }
    if (fast)
        attn_kernel<<<kGrid, kThreads, kSmemBytes>>>(Scalars{{ksc, kzp, vsc, vzp}}, qk, by_sm, kcos, ksin, qv, q, qcos, qsin,
                                                     (__nv_bfloat16*)d_out, tmv);
    else
        attn_fallback<<<kNH, 256>>>(q, qk, ksc, kzp, qv, vsc, vzp, qcos, qsin, kcos, ksin, (__nv_bfloat16*)d_out);
}
```

```cpp
#include <cuda_runtime.h>
#include <cuda.h>
#include <cuda_bf16.h>
#include <stdint.h>

namespace {

constexpr int kB = 8, kH = 32, kS = 2048, kD = 192;
constexpr int kNH = kB * kH;
constexpr int kTeams = 4;
constexpr int kSlots = 32;
constexpr int kRows = kS / kSlots;
constexpr int kRounds = kNH / kTeams;
constexpr int kStream = kTeams * kSlots;
constexpr int kGrid = kStream + kTeams;
constexpr int kCW = 16;
constexpr int kR = kRows / kCW;
constexpr int kNP = 2;
constexpr int kThreads = (kCW + 2 + kNP) * 32;
constexpr int kRowBytes = kD * 4;
constexpr int kChunk = kRows * kRowBytes;
constexpr int kNS = 3;
constexpr int kHalf = kChunk / 2;
constexpr int kHRows = kRows / 2;
constexpr int kLead = 250;
constexpr int kLeadEnd = 215;
constexpr int kRampEnd = 12, kRampStep = 70;
constexpr int kWaveSlot = 2, kWaveHalf = 40, kWaveV = 16, kWaveRamp = 8;
constexpr uint32_t kRate = 69, kAhead = 256;
constexpr int kPollSleep = 300;
constexpr int kQuick = 20;
constexpr int kSleep = 200;
constexpr int kPR = 12;
constexpr int kScStride = 196;
constexpr int kOffScal = kNS * kChunk;
constexpr int kOffQ = kOffScal + kRounds * 4 * kRows * 2;
constexpr int kOffSc = kOffQ + kRounds * kD * 2;
constexpr int kOffBar = kOffSc + 2 * kCW * kScStride * 4;
constexpr int kF = 3;
constexpr int kFG = 4;
constexpr int kFW = kD / kFG;
constexpr int kFRows = kRows * kFG;
constexpr int kFHeads = kSlots / kFG;
constexpr int kDef0 = 16;
constexpr int kEarly = 4;
constexpr int kFBoxes = 16;
constexpr int kPrep = 40;
constexpr int kOffW = kOffScal;
constexpr int kOffFin = kOffW + kF * kFRows * 4;
constexpr int kPartStride = 20, kPartOdd = (kFW / 2) * kPartStride + 16, kPartSize = 2 * kPartOdd;
constexpr int kOffPart = kOffFin + kFW * 4;
constexpr int kOffMisc = kOffBar + (4 * kNS + 6 + kF * kFBoxes) * 8;
constexpr int kOffMax = kOffMisc + 32;
constexpr int kSmemBytes = kOffMax + 4 * kCW * 4;
constexpr int kRecWords = 112;
constexpr int kMG = 6;
static_assert(kNS >= 3, "ring");
static_assert(kOffBar % 8 == 0 && kOffSc % 16 == 0 && kOffMax % 16 == 0, "alignment");
static_assert(kPR % kMG == 0, "ring");
static_assert(kNP == 2 && kOffMisc % 16 == 0 && kLeadEnd >= kStream && kS == kFHeads * kFRows && kFHeads == 8, "schedule");
static_assert(kSmemBytes <= 232448, "smem");
static_assert(kDef0 + kFHeads < kPrep && kPrep + 16 + 3 < kRounds && kEarly + kF * kFBoxes + 3 < kRounds && kOffPart <= kOffScal + (kPrep - 2) * 4 * kRows * 2 &&
              kOffPart + kF * kPartSize * 4 <= kOffScal + (kRounds - 2) * 4 * kRows * 2 && kF <= kNS && kFBoxes == kCW, "deferred rounds");

__device__ __align__(128) unsigned long long g_rec[kPR * kStream * kRecWords];
__device__ __align__(128) unsigned long long g_pre[kTeams * kFHeads * kRecWords];
__device__ __align__(128) unsigned long long g_lg[kTeams * kFHeads * kF * kFRows];
__device__ __align__(8192) unsigned int g_prog[kNP * 1024];
__device__ __align__(128) unsigned int g_epoch;
__device__ __align__(128) unsigned int g_arrive;
__device__ __align__(128) unsigned int g_mdone[kTeams * kMG * 32];

constexpr int kSpin = 1 << 24;

__device__ __forceinline__ uint32_t clock32() {
    uint32_t t;
    asm volatile("mov.u32 %0, %%clock;" : "=r"(t)::"memory");
    return t;
}
__device__ __forceinline__ uint32_t s2u(const void* p) { return (uint32_t)__cvta_generic_to_shared(p); }
__device__ __forceinline__ void mbar_init(uint32_t a, int c) {
    asm volatile("mbarrier.init.shared::cta.b64 [%0], %1;" ::"r"(a), "r"(c));
}
__device__ __forceinline__ void mbar_wait(uint32_t a, uint32_t ph) {
    uint32_t ok;
    for (int it = 0;; it++) {
        asm volatile(
            "{\n.reg .pred p;\nmbarrier.try_wait.parity.shared::cta.b64 p, [%1], %2;\nselp.u32 %0, 1, 0, p;\n}"
            : "=r"(ok) : "r"(a), "r"(ph) : "memory");
        if (ok) break;
        if (it > kSpin) __trap();
    }
}
__device__ __forceinline__ void mbar_arrive(uint32_t a) {
    asm volatile("mbarrier.arrive.shared::cta.b64 _, [%0];" ::"r"(a) : "memory");
}
__device__ __forceinline__ void mbar_expect(uint32_t a, uint32_t bytes) {
    asm volatile("mbarrier.arrive.expect_tx.shared::cta.b64 _, [%0], %1;" ::"r"(a), "r"(bytes) : "memory");
}
__device__ __forceinline__ void bulk_g2s_stream(uint32_t dst, const void* src, uint32_t bytes, uint32_t mbar, uint64_t pol) {
    asm volatile("cp.async.bulk.shared::cluster.global.mbarrier::complete_tx::bytes.L2::cache_hint [%0], [%1], %2, [%3], %4;"
                 ::"r"(dst), "l"(src), "r"(bytes), "r"(mbar), "l"(pol) : "memory");
}
__device__ __forceinline__ void bulk_g2s(uint32_t dst, const void* src, uint32_t bytes, uint32_t mbar) {
    asm volatile("cp.async.bulk.shared::cluster.global.mbarrier::complete_tx::bytes [%0], [%1], %2, [%3];"
                 ::"r"(dst), "l"(src), "r"(bytes), "r"(mbar) : "memory");
}
__device__ __forceinline__ void cp16(uint32_t dst, const void* src) {
    asm volatile("cp.async.cg.shared.global [%0], [%1], 16;" ::"r"(dst), "l"(src) : "memory");
}
__device__ __forceinline__ float bf_lo(uint32_t u) { return __uint_as_float(u << 16); }
__device__ __forceinline__ float bf_hi(uint32_t u) { return __uint_as_float(u & 0xffff0000u); }
__device__ __forceinline__ float bf_round(float x) { return __bfloat162float(__float2bfloat16_rn(x)); }
__device__ __forceinline__ uint32_t ld_pair(const __nv_bfloat16* p) {
    return __ldg(reinterpret_cast<const uint32_t*>(p));
}
__device__ __forceinline__ unsigned int ld_relaxed(const unsigned int* p) {
    unsigned int v;
    asm volatile("ld.relaxed.gpu.global.u32 %0, [%1];" : "=r"(v) : "l"(p) : "memory");
    return v;
}
__device__ __forceinline__ unsigned long long pack_rec(float a, float b, uint32_t tag) {
    const uint32_t x = (__float_as_uint(a) & ~15u) | (tag & 15u), y = (__float_as_uint(b) & ~15u) | (tag >> 4);
    return ((unsigned long long)y << 32) | x;
}
__device__ __forceinline__ void st_rec(unsigned long long* p, float a, float b, uint32_t tag) {
    asm volatile("st.relaxed.gpu.global.b64 [%0], %1;" ::"l"(p), "l"(pack_rec(a, b, tag)) : "memory");
}
__device__ __forceinline__ float rec_lo(unsigned long long w) { return __uint_as_float((uint32_t)w & ~15u); }
__device__ __forceinline__ float rec_hi(unsigned long long w) { return __uint_as_float((uint32_t)(w >> 32) & ~15u); }
__device__ __forceinline__ unsigned long long ld_rec1(const unsigned long long* p) {
    unsigned long long x;
    asm volatile("ld.relaxed.gpu.global.b64 %0, [%1];" : "=l"(x) : "l"(p) : "memory");
    return x;
}
__device__ __forceinline__ void ld_rec2(const unsigned long long* p, unsigned long long& x, unsigned long long& y) {
    asm volatile("ld.relaxed.gpu.global.v2.b64 {%0, %1}, [%2];" : "=l"(x), "=l"(y) : "l"(p) : "memory");
}
__device__ __forceinline__ uint32_t rec_bad(unsigned long long w, uint32_t tlo, uint32_t thi) {
    return (((uint32_t)w ^ tlo) | ((uint32_t)(w >> 32) ^ thi)) & 15u;
}
__device__ __forceinline__ void st_ml(unsigned long long* p, float m, float l, uint32_t tag) {
    const uint32_t y = ((__float_as_uint(l) + 0x80u) & ~0xffu) | tag;
    asm volatile("st.relaxed.gpu.global.b64 [%0], %1;" ::"l"(p), "l"(((unsigned long long)y << 32) | __float_as_uint(m)) : "memory");
}
__device__ __forceinline__ uint32_t ml_bad(unsigned long long w, uint32_t tag) { return ((uint32_t)(w >> 32) ^ tag) & 0xffu; }
__device__ __forceinline__ float ml_m(unsigned long long w) { return __uint_as_float((uint32_t)w); }
__device__ __forceinline__ float ml_l(unsigned long long w) { return __uint_as_float((uint32_t)(w >> 32) & ~0xffu); }
__device__ __forceinline__ float warp_max(float v) {
    const int b = __float_as_int(v);
    const int k = __reduce_max_sync(0xffffffffu, b ^ ((b >> 31) & 0x7fffffff));
    return __int_as_float(k ^ ((k >> 31) & 0x7fffffff));
}
__device__ __forceinline__ uint32_t round_tag(unsigned int epoch, int r) {
    constexpr unsigned kUses = (kRounds + kPR - 1) / kPR;
    return (epoch * kUses + (unsigned)(r / kPR)) % 255u + 1u;
}

__device__ __forceinline__ void rotate_q(uint32_t* qrow, int p, uint32_t c_lo, uint32_t c_hi, uint32_t s_lo, uint32_t s_hi) {
    const uint32_t lo = qrow[p], hi = qrow[p + 48];
    const float a0 = bf_round(bf_lo(lo) * bf_lo(c_lo)) + bf_round(-bf_lo(hi) * bf_lo(s_lo));
    const float a1 = bf_round(bf_hi(lo) * bf_hi(c_lo)) + bf_round(-bf_hi(hi) * bf_hi(s_lo));
    const float b0 = bf_round(bf_lo(hi) * bf_lo(c_hi)) + bf_round(bf_lo(lo) * bf_lo(s_hi));
    const float b1 = bf_round(bf_hi(hi) * bf_hi(c_hi)) + bf_round(bf_hi(lo) * bf_hi(s_hi));
    const __nv_bfloat162 ua = __floats2bfloat162_rn(a0, a1), ub = __floats2bfloat162_rn(b0, b1);
    qrow[p] = *reinterpret_cast<const uint32_t*>(&ua);
    qrow[p + 48] = *reinterpret_cast<const uint32_t*>(&ub);
}
__device__ __forceinline__ int deferred_to(int blk, int r) {
    return (unsigned)(r - kDef0) < (unsigned)kFHeads ? (blk - kF * (r - kDef0)) & (kFHeads - 1) : kF;
}

__device__ __forceinline__ unsigned role_of_sm(unsigned smid) {
    const unsigned u = smid >> 1;
    const unsigned g = u < 32 ? u & 7 : u < 60 ? 1 + (u - 32) % 7 : u < 62 ? u - 54 : 0;
    const unsigned t = u < 32 ? u >> 3 : u < 60 ? 4 + (u - 32) / 7 : u < 62 ? 8 : u - 58;
    const unsigned lin = 16 * g + (g == 7 ? 2 : 0) + 2 * t + (smid & 1);
    return lin < 2 ? lin + kStream : lin < 48 ? lin - 2 : lin < 50 ? lin + (kStream + 2 - 48) : lin - 4;
}
static_assert(kGrid == 132 && kTeams == 4, "role_of_sm");
struct Scalars { const __nv_bfloat16* p[4]; };

__global__ void __launch_bounds__(kThreads, 1)
attn_kernel(const __grid_constant__ Scalars scal, const int* __restrict__ qk, int by_sm, const __nv_bfloat16* __restrict__ kcos,
            const __nv_bfloat16* __restrict__ ksin, const int* __restrict__ qv, const __nv_bfloat16* __restrict__ q,
            const __nv_bfloat16* __restrict__ qcos, const __nv_bfloat16* __restrict__ qsin,
            __nv_bfloat16* __restrict__ out, const __grid_constant__ CUtensorMap tmv) {
    extern __shared__ __align__(128) unsigned char smem[];
    const int warp = threadIdx.x >> 5, lane = threadIdx.x & 31;
    const uint32_t full0 = s2u(smem + kOffBar), empty0 = full0 + 2 * kNS * 8;
    const uint32_t sfull = empty0 + 2 * kNS * 8, sempty = sfull + 16, mxbar = sempty + 16, fine = mxbar + 16;
    volatile unsigned int* s_misc = reinterpret_cast<volatile unsigned int*>(smem + kOffMisc);
    uint64_t pol = 0;

    if (threadIdx.x == kCW * 32 && blockIdx.x < kStream)
        asm volatile("cp.async.bulk.prefetch.L2.global [%0], %1;"
                     ::"l"(scal.p[blockIdx.x & 3] + (blockIdx.x >> 2) * (kNH * kS * 4 / kStream)), "n"(kNH * kS * 4 / kStream * 2) : "memory");
    unsigned bid = blockIdx.x;
    if (by_sm) {
        unsigned smid, nsm;
        asm volatile("mov.u32 %0, %%smid;" : "=r"(smid));
        asm volatile("mov.u32 %0, %%nsmid;" : "=r"(nsm));
        if (nsm == kGrid) bid = role_of_sm(smid);
    }
    if (threadIdx.x == kCW * 32 && bid < kStream) {
        const int m = bid % kSlots;
        const uint32_t sm0 = s2u(smem);
        for (int i = 0; i < 2 * kNS; i++) mbar_init(full0 + 8 * i, 1);
        asm volatile("fence.mbarrier_init.release.cluster;" ::: "memory");
        asm volatile("createpolicy.fractional.L2::evict_first.b64 %0, 1.0;" : "=l"(pol));
        const int* k0 = qk + (size_t)(bid / kSlots * kS + m * kHRows) * kD;
#pragma unroll
        for (int h = 0; h < 2; h++) {
            mbar_expect(full0 + 16 + 8 * h, kHalf);
            bulk_g2s_stream(sm0 + kChunk + h * kHalf, k0 + h * (kS / 2 * kD), kHalf, full0 + 16 + 8 * h, pol);
        }
#pragma unroll
        for (int h = 0; h < 2; h++) {
            mbar_expect(full0 + 8 * h, kHalf);
            bulk_g2s(sm0 + h * kHalf, kcos + (h * (kS / 2) + m * kHRows) * kD, kHalf / 2, full0 + 8 * h);
            bulk_g2s(sm0 + h * kHalf + kHalf / 2, ksin + (h * (kS / 2) + m * kHRows) * kD, kHalf / 2, full0 + 8 * h);
        }
#pragma unroll
        for (int h = 0; h < 2; h++) {
            mbar_expect(full0 + 32 + 8 * h, kHalf);
            bulk_g2s_stream(sm0 + 2 * kChunk + h * kHalf, k0 + (kTeams * kS + h * (kS / 2)) * kD, kHalf, full0 + 32 + 8 * h, pol);
        }
    }

    if (bid >= kStream) {
        const int team = bid - kStream;
        if (threadIdx.x == 0) s_misc[0] = ld_relaxed(&g_epoch);
        __syncthreads();
        if (threadIdx.x == 0 && atomicAdd(&g_arrive, 1u) == kGrid - 1) { g_arrive = 0u; g_epoch = s_misc[0] + 1u; }
        if (warp >= 3 * kMG) return;
        const int grp = warp / 3, t = threadIdx.x - grp * 96;
        constexpr int kRecBytes = kSlots * kRecWords * 8;
        if (t == 0) {
            mbar_init(s2u(smem + kOffBar) + grp * 8, 1);
            asm volatile("fence.mbarrier_init.release.cluster;" ::: "memory");
        }
        asm volatile("bar.sync %0, 96;" ::"r"(3 + grp) : "memory");
        for (int r = grp; r < kRounds; r += kMG) {
            const int g = r % kMG;
            const int tt = threadIdx.x - g * 96, qd = tt % 48, half = tt / 48;
            const uint32_t tag = round_tag(s_misc[0], r);
            const uint32_t tlo = tag & 15u, thi = tag >> 4;
            const unsigned long long* rec = g_rec + ((size_t)(r % kPR) * kStream + team * kSlots) * kRecWords;
            unsigned long long ml, x[16], y[16];
            {
                const unsigned long long* buf = reinterpret_cast<const unsigned long long*>(smem + g * kRecBytes);
                const uint32_t mb = s2u(smem + kOffBar) + g * 8;
                if (tt < 32) {
                    const int want = r == kRounds - 1 ? kQuick : kSlots;
                    for (int i2 = 0;; i2++) {
                        ml = ld_rec1(rec + lane * kRecWords + 96);
                        if (__popc(__ballot_sync(0xffffffffu, ml_bad(ml, tag) == 0)) >= want) break;
                        if (i2 > kSpin) __trap();
                        __nanosleep(kSleep);
                    }
                    if (tt == 0) {
                        mbar_expect(mb, kRecBytes);
                        bulk_g2s(s2u(buf), rec, kRecBytes, mb);
                    }
                }
                mbar_wait(mb, (r / kMG) & 1);
                ml = buf[lane * kRecWords + 96];
#pragma unroll
                for (int i = 0; i < 16; i++) {
                    const ulonglong2 u = *reinterpret_cast<const ulonglong2*>(buf + (half * 16 + i) * kRecWords + 2 * qd);
                    x[i] = u.x; y[i] = u.y;
                }
                const unsigned long long* po = rec + half * 16 * kRecWords + 2 * qd;
                for (int it = 0;; it++) {
                    uint32_t any = ml_bad(ml, tag);
                    if (any) ml = ld_rec1(rec + lane * kRecWords + 96);
#pragma unroll
                    for (int i = 0; i < 16; i++) {
                        const uint32_t bad = rec_bad(x[i], tlo, thi) | rec_bad(y[i], tlo, thi);
                        if (bad) ld_rec2(po + i * kRecWords, x[i], y[i]);
                        any |= bad;
                    }
                    if (__all_sync(0xffffffffu, any == 0)) break;
                    if (it > kSpin) __trap();
                }
            }
            const float M = ml_m(ml);
            const float MM = warp_max(M);
            const float w = exp2f(M - MM);
            float LL = w * ml_l(ml);
#pragma unroll
            for (int o = 16; o > 0; o >>= 1) LL += __shfl_xor_sync(0xffffffffu, LL, o);
            float4 a = make_float4(0.f, 0.f, 0.f, 0.f);
#pragma unroll
            for (int i = 0; i < 16; i++) {
                const float wi = __shfl_sync(0xffffffffu, w, half * 16 + i);
                a.x = fmaf(wi, rec_lo(x[i]), a.x);
                a.y = fmaf(wi, rec_hi(x[i]), a.y);
                a.z = fmaf(wi, rec_lo(y[i]), a.z);
                a.w = fmaf(wi, rec_hi(y[i]), a.w);
            }
            float* rb = reinterpret_cast<float*>(smem + kMG * kRecBytes) + (2 * g + ((r / kMG) & 1)) * kD + 4 * qd;
            if (half == 1) *reinterpret_cast<float4*>(rb) = a;
            asm volatile("bar.sync %0, 96;" ::"r"(3 + g) : "memory");
            if (half == 0) {
                const float4 u = *reinterpret_cast<float4*>(rb);
                if ((unsigned)(r - kDef0) < (unsigned)kFHeads) {
                    unsigned long long* pre = g_pre + (size_t)(team * kFHeads + r - kDef0) * kRecWords;
                    const uint32_t ptag = s_misc[0] % 255u + 1u;
                    st_rec(pre + 2 * qd, a.x + u.x, a.y + u.y, ptag);
                    st_rec(pre + 2 * qd + 1, a.z + u.z, a.w + u.w, ptag);
                    if (qd == 0) st_ml(pre + 96, MM, LL, ptag);
                } else {
                    const float inv = __fdividef(1.0f, LL);
                    const __nv_bfloat162 o0 = __floats2bfloat162_rn((a.x + u.x) * inv, (a.y + u.y) * inv);
                    const __nv_bfloat162 o1 = __floats2bfloat162_rn((a.z + u.z) * inv, (a.w + u.w) * inv);
                    uint2 ov;
                    ov.x = *reinterpret_cast<const uint32_t*>(&o0);
                    ov.y = *reinterpret_cast<const uint32_t*>(&o1);
                    *reinterpret_cast<uint2*>(out + (size_t)(kTeams * r + team) * kD + 4 * qd) = ov;
                }
            }
            if (tt == 95)
                asm volatile("st.relaxed.gpu.global.u32 [%0], %1;" ::"l"(&g_mdone[(team * kMG + g) * 32]), "r"(s_misc[0] * kRounds + r + 1) : "memory");
        }
        return;
    }

    const int m = bid % kSlots, team = bid / kSlots;
    const int row0 = m * kHRows;

    if (warp == kCW) {
        unsigned int epoch = 0;
        const size_t off0 = ((size_t)team * kS + row0) * kD;
        const uint32_t sm0 = s2u(smem);
        if (lane == 0) {
            epoch = ld_relaxed(&g_epoch);
            s_misc[0] = epoch;
            s_misc[1] = 0;
            for (int j = 0; j < kNP; j++) {
                s_misc[4 + 2 * j] = epoch * (kStream * (4 * kRounds - 2));
                s_misc[5 + 2 * j] = clock32();
            }
        }
        __syncwarp();
        asm volatile("bar.sync 2, %0;" ::"n"(kThreads) : "memory");
        if (lane == 0) {
            const unsigned int base = epoch * (kStream * (4 * kRounds - 2));
            const int phase = (2 * team - (kTeams - 1)) * (kStream / 2) + (m - kSlots / 2) * kWaveSlot;
            int use0 = kNS, use1 = kNS;
            const int* kp = qk + off0;
            const int* vp = qv + off0;
            for (int ph2 = 4; ph2 < 2 * (2 * kRounds + kF); ph2++) {
                const int p = ph2 >> 1, h = ph2 & 1;
                const bool isv = (p & 1) == 0 || p == 2 * kRounds - 1;
                const int r = p == 2 * kRounds - 1 ? kRounds - 1 : isv ? (p >> 1) - 1 : (p + 1) >> 1;
                const int ramp = max(min(min(ph2 - 4, 4 * kRounds - ph2), kWaveRamp), 0);
                const int tau = kStream * ph2 + (phase + (h ? -kWaveHalf : kWaveHalf) + (isv ? kWaveV : -kWaveV)) * ramp / kWaveRamp;
                const int gone = min(max(tau - kStream * (4 * kDef0 + 3), 0), 4 * kStream * kFHeads) * kF / (2 * kFHeads);
                const unsigned int need = base + tau - gone - max(kRampEnd - ph2, 0) * kRampStep - (p >= 2 * kRounds ? kLeadEnd : kLead);
                const bool skip = isv && deferred_to(4 * h + m / 8, r) < kF;
                const int u = h ? use1 : use0;
                const int slot = u >= kNS ? u - kNS : u;
                const uint32_t dst = sm0 + slot * kChunk + h * kHalf, fullb = full0 + 16 * slot + 8 * h;
                const int* src = (isv ? vp : kp) + (size_t)(r * kTeams * kS + h * (kS / 2)) * kD;
                if (!skip) {
                    const int un = u + 1 == 2 * kNS ? 0 : u + 1;
                    if (h) use1 = un; else use0 = un;
                    mbar_wait(fullb + 2 * kNS * 8, u >= kNS ? 0 : 1);
                    if (p < 2 * kRounds) mbar_expect(fullb, kHalf);
                }
                asm volatile("" ::"l"(src), "r"(dst) : "memory");
                if (!skip)
                    for (int it = 0;; it++) {
                        uint32_t x, tx, y, ty;
                        asm volatile("ld.volatile.shared.v4.u32 {%0, %1, %2, %3}, [%4];"
                                     : "=r"(x), "=r"(tx), "=r"(y), "=r"(ty) : "r"(sm0 + kOffMisc + 16) : "memory");
                        const uint32_t now = clock32();
                        x += min(((now - tx) * kRate) >> 10, kAhead);
                        y += min(((now - ty) * kRate) >> 10, kAhead);
                        if ((int)((x - need) & (y - need)) >= 0) break;
                        if (it > 16 * kSpin) __trap();
                    }
                if (ph2 == 2 * (2 * kRounds + kF) - 1) s_misc[1] = 1;
                if (p >= 2 * kRounds || skip) {
                    const int hi = m / kFG;
                    const int row = (kTeams * (kDef0 + hi) + team) * kS + ((kF * hi + p - 2 * kRounds) & (kFHeads - 1)) * kFRows + h * (kFRows / 2);
                    const uint32_t fb = fine + 8 * (kFBoxes / 2) * (ph2 - 4 * kRounds);
#pragma unroll 1
                    for (int w = 0; w < kFBoxes / 2; w++)
                        asm volatile("{\n.reg .pred p;\nsetp.ne.u32 p, %6, 0;\n"
                                     "@p cp.async.bulk.tensor.2d.shared::cluster.global.tile.mbarrier::complete_tx::bytes.L2::cache_hint [%0], [%1, {%2, %3}], [%4], %5;\n}"
                                     ::"r"(dst + w * (kChunk / kFBoxes)), "l"(&tmv), "r"((m % kFG) * kFW), "r"(row + w * (kFRows / kFBoxes)),
                                       "r"(fb + 8 * w), "l"(pol), "r"((uint32_t)!skip) : "memory");
                } else {
                    bulk_g2s_stream(dst, src, kHalf, fullb, pol);
                }
            }
        }
    } else if (warp >= kCW + 2) {
        asm volatile("bar.sync 2, %0;" ::"n"(kThreads) : "memory");
        if (lane == 0) {
            const int j = warp - (kCW + 2);
            for (int it = 0; !s_misc[1]; it++) {
                const uint32_t t = clock32();
                const uint32_t v = ld_relaxed(g_prog + j * 1024);
                asm volatile("st.volatile.shared.v2.u32 [%0], {%1, %2};" ::"r"(s2u(smem) + kOffMisc + 16 + 8 * j), "r"(v), "r"(t) : "memory");
                if (s_misc[1]) break;
                if (it > kSpin) __trap();
                __nanosleep(kPollSleep);
            }
        }
    } else if (warp == kCW + 1) {
        {
            if (lane < 2 * kNS + 6) mbar_init(empty0 + 8 * lane, lane < 2 * kNS ? kCW / 2 : (lane >= 2 * kNS + 2 && lane < 2 * kNS + 4) ? 1 : kCW);
            asm volatile("fence.mbarrier_init.release.cluster;" ::: "memory");
        }
        asm volatile("bar.sync 2, %0;" ::"n"(kThreads) : "memory");
        const unsigned int epoch = s_misc[0];
        if (lane == 0 && atomicAdd(&g_arrive, 1u) == kGrid - 1) { g_arrive = 0u; g_epoch = epoch + 1u; }
        {
            const uint32_t sm0 = s2u(smem);
            const __nv_bfloat16* src = scal.p[lane >> 3] + (size_t)team * kS + row0 + (lane & 4) * (kS / 8) + (lane & 3) * 8;
            const __nv_bfloat16* qs = q + team * kD + lane * 8;
#pragma unroll 1
            for (int r = kEarly; r < kRounds; r++) {
                cp16(sm0 + kOffScal + r * 512 + lane * 16, src + (size_t)r * (kTeams * kS));
                if (lane < 24) cp16(sm0 + kOffQ + r * (kD * 2) + lane * 16, qs + r * (kTeams * kD));
                if (r == 2 * kEarly - 1 || r == kRounds - 1) asm volatile("cp.async.commit_group;" ::: "memory");
            }
        }
        uint32_t cs[2][4];
#pragma unroll
        for (int i = 0; i < 2; i++) {
            const int p = (lane + 32 * i) % 48;
            cs[i][0] = ld_pair(qcos + 2 * p); cs[i][1] = ld_pair(qcos + 2 * p + 96);
            cs[i][2] = ld_pair(qsin + 2 * p); cs[i][3] = ld_pair(qsin + 2 * p + 96);
        }
        asm volatile("cp.async.wait_group 1;" ::: "memory");
        __syncwarp();
        for (int r = 0; r < kRounds; r++) {
            const float* sc = reinterpret_cast<const float*>(smem + kOffSc) + (r & 1) * (kCW * kScStride);
            const uint32_t tag = round_tag(epoch, r);
            unsigned long long* rec = g_rec + ((size_t)(r % kPR) * kStream + team * kSlots + m) * kRecWords;
            if (r >= kEarly && r < kEarly + kF * kFBoxes && lane == 0) {
                mbar_init(fine + 8 * (r - kEarly), 1);
                asm volatile("fence.mbarrier_init.release.cluster;" ::: "memory");
                mbar_expect(fine + 8 * (r - kEarly), kChunk / kFBoxes);
                asm volatile("fence.proxy.async.shared::cta;" ::: "memory");
            }
            if (r == kPrep + m / 2) {
                const unsigned long long* pre = g_pre + (size_t)(team * kFHeads + m / kFG) * kRecWords;
                const unsigned long long* lgp = g_lg + (size_t)(team * kFHeads + m / kFG) * (kF * kFRows);
                const uint32_t ptag = epoch % 255u + 1u;
                unsigned long long ml, po;
                for (int it = 0;; it++) {
                    ml = ld_rec1(pre + 96);
                    po = ld_rec1(pre + (m % kFG) * (kFW / 2) + lane % (kFW / 2));
                    if (!(ml_bad(ml, ptag) | rec_bad(po, ptag & 15u, ptag >> 4))) break;
                    if (it > kSpin) __trap();
                }
                const float inv = 1.0f / ml_l(ml);
                if (lane < kFW / 2) {
                    reinterpret_cast<float2*>(smem + kOffFin)[lane] = make_float2(rec_lo(po) * inv, rec_hi(po) * inv);
                }
#pragma unroll 1
                for (int c = 0; c < kF; c++) {
                    unsigned long long u[8];
                    for (int it = 0;; it++) {
                        uint32_t bad = 0;
#pragma unroll
                        for (int k = 0; k < 8; k++) {
                            u[k] = ld_rec1(lgp + c * kFRows + 32 * k + lane);
                            bad |= ml_bad(u[k], ptag);
                        }
                        if (!bad) break;
                        if (it > kSpin) __trap();
                    }
#pragma unroll
                    for (int k = 0; k < 8; k++)
                        reinterpret_cast<float*>(smem + kOffW)[c * kFRows + 32 * k + lane] = ml_l(u[k]) * exp2f(ml_m(u[k]) - ml_m(ml)) * inv;
                }
                __syncwarp();
            }
            if (r == kRounds - 3 && lane == 0) asm volatile("prefetch.tensormap [%0];" ::"l"(&tmv) : "memory");
            if (r == kEarly) {
                asm volatile("cp.async.wait_all;" ::: "memory");
                __syncwarp();
            }
            if (r + kEarly < kRounds) {
                uint32_t* qrow = reinterpret_cast<uint32_t*>(smem + kOffQ + (r + kEarly) * (kD * 2));
                rotate_q(qrow, lane, cs[0][0], cs[0][1], cs[0][2], cs[0][3]);
                if (lane < 16) rotate_q(qrow, lane + 32, cs[1][0], cs[1][1], cs[1][2], cs[1][3]);
            }
            if (r >= kPR) {
                const unsigned int* mdone = &g_mdone[(team * kMG + r % kMG) * 32];
                const unsigned int need = epoch * kRounds + r - kPR + 1;
                for (int it = 0; (int)(ld_relaxed(mdone) - need) < 0; it++)
                    if (it > kSpin) __trap();
            }
            mbar_wait(sfull + 8 * (r & 1), (r >> 1) & 1);
            const float M = sc[0];
            float L = lane < kCW ? sc[lane * kScStride + 1] : 0.f;
            float acc[2][6];
#pragma unroll
            for (int ww = 0; ww < kCW; ww++) {
#pragma unroll
                for (int j = 0; j < 3; j++) {
                    const float2 t = *reinterpret_cast<const float2*>(sc + ww * kScStride + 4 + 64 * j + 2 * lane);
                    acc[ww & 1][2 * j] = ww < 2 ? t.x : acc[ww & 1][2 * j] + t.x;
                    acc[ww & 1][2 * j + 1] = ww < 2 ? t.y : acc[ww & 1][2 * j + 1] + t.y;
                }
                if ((ww & 3) == 3 && ww < 15) L += __shfl_xor_sync(0xffffffffu, L, 8 >> (ww >> 2));
            }
            L += __shfl_xor_sync(0xffffffffu, L, 1);
#pragma unroll
            for (int j = 0; j < 3; j++)
                st_rec(rec + 32 * j + lane, acc[0][2 * j] + acc[1][2 * j], acc[0][2 * j + 1] + acc[1][2 * j + 1], tag);
            if (lane == 0) st_ml(rec + 96, M, L, tag);
            __syncwarp();
            if (lane == 0) mbar_arrive(sempty + 8 * (r & 1));
        }
    } else {
        int dp[3];
#pragma unroll
        for (int j = 0; j < 3; j++) dp[j] = (64 * j + 2 * lane + 96) % kD;
        {
            const uint32_t sm0 = s2u(smem);
            if (warp < kEarly) {
                cp16(sm0 + kOffScal + threadIdx.x * 16, scal.p[lane >> 3] + (size_t)(kTeams * warp + team) * kS + row0 + (lane & 4) * (kS / 8) + (lane & 3) * 8);
            } else if (warp < 2 * kEarly && lane < 24) {
                cp16(sm0 + kOffQ + (warp - kEarly) * (kD * 2) + lane * 16, q + (size_t)(kTeams * (warp - kEarly) + team) * kD + lane * 8);
            }
            asm volatile("cp.async.commit_group;" ::: "memory");
        }
        const int p = threadIdx.x % 48, g = threadIdx.x / 48;
        const uint32_t c_lo = ld_pair(qcos + 2 * p), c_hi = ld_pair(qcos + 2 * p + 96);
        const uint32_t s_lo = ld_pair(qsin + 2 * p), s_hi = ld_pair(qsin + 2 * p + 96);
        float kc[kR][6], ks[kR][6];
        asm volatile("bar.sync 2, %0;" ::"n"(kThreads) : "memory");
        const int half = warp / (kCW / 2);
        const uint32_t fullh = full0 + 8 * half, emptyh = empty0 + 8 * half;
        mbar_wait(fullh, 0);
#pragma unroll
        for (int i = 0; i < kR; i++) {
            const unsigned char* cb = smem + half * (kHalf / 2) + (warp * kR + i) * (kD * 2);
#pragma unroll
            for (int j = 0; j < 3; j++) {
                const uint32_t uc = *reinterpret_cast<const uint32_t*>(cb + 128 * j + 4 * lane);
                const uint32_t us = *reinterpret_cast<const uint32_t*>(cb + kHalf / 2 + 2 * dp[j]);
                kc[i][2 * j] = bf_lo(uc); kc[i][2 * j + 1] = bf_hi(uc);
                const float sg = (j == 0 || (j == 1 && lane < 16)) ? 1.f : -1.f;
                ks[i][2 * j] = sg * bf_lo(us); ks[i][2 * j + 1] = sg * bf_hi(us);
            }
        }
        __syncwarp();
        if (lane == 0) mbar_arrive(emptyh);
        asm volatile("cp.async.wait_group 0;" ::: "memory");
        asm volatile("bar.sync 1, %0;" ::"n"(kCW * 32) : "memory");
        if (g < kEarly) rotate_q(reinterpret_cast<uint32_t*>(smem + kOffQ + g * (kD * 2)), p, c_lo, c_hi, s_lo, s_hi);
        asm volatile("bar.sync 1, %0;" ::"n"(kCW * 32) : "memory");
        const float scale_log2e = 1.4426950408889634f * rsqrtf((float)kD);
        float* my0 = reinterpret_cast<float*>(smem + kOffSc) + warp * kScStride;

        float* s_max = reinterpret_cast<float*>(smem + kOffMax);
        int slot = 1;
        uint32_t ph = 0;
        float lgc[kR] = {0.f, 0.f, 0.f, 0.f};
        for (int it = 0; it <= kRounds; it++) {
            float lg[kR];
            if (it < kRounds) {
                float qa[6], qb[6];
#pragma unroll
                for (int j = 0; j < 3; j++) {
                    const uint32_t qo = *reinterpret_cast<const uint32_t*>(smem + kOffQ + it * (kD * 2) + 2 * (64 * j + 2 * lane));
                    const uint32_t qp = *reinterpret_cast<const uint32_t*>(smem + kOffQ + it * (kD * 2) + 2 * dp[j]);
                    qa[2 * j] = bf_lo(qo); qa[2 * j + 1] = bf_hi(qo);
                    qb[2 * j] = bf_lo(qp); qb[2 * j + 1] = bf_hi(qp);
                }
                const unsigned char* sp = smem + kOffScal + it * (4 * kRows * 2) + warp * (kR * 2);
                const uint2 uks = *reinterpret_cast<const uint2*>(sp);
                const uint2 ukz = *reinterpret_cast<const uint2*>(sp + kRows * 2);
                const float kz[4] = {bf_lo(ukz.x), bf_hi(ukz.x), bf_lo(ukz.y), bf_hi(ukz.y)};
                const float sk[4] = {bf_lo(uks.x), bf_hi(uks.x), bf_lo(uks.y), bf_hi(uks.y)};
                mbar_wait(fullh + 16 * slot, ph);
                if ((threadIdx.x & 255) < kNP) asm volatile("red.relaxed.gpu.global.add.u32 [%0], 1;" ::"l"(g_prog + lane * 1024) : "memory");
                const unsigned char* kb = smem + slot * kChunk + warp * (kR * kRowBytes) + lane * 8;
#pragma unroll
                for (int i = 0; i < kR; i++) {
                    float dot = 0.f;
#pragma unroll
                    for (int j = 0; j < 3; j++) {
                        const int2 kk = *reinterpret_cast<const int2*>(kb + i * kRowBytes + 256 * j);
                        const float e0 = qa[2 * j] * kc[i][2 * j] + qb[2 * j] * ks[i][2 * j];
                        const float e1 = qa[2 * j + 1] * kc[i][2 * j + 1] + qb[2 * j + 1] * ks[i][2 * j + 1];
                        dot = fmaf((float)kk.x - kz[i], e0, dot);
                        dot = fmaf((float)kk.y - kz[i], e1, dot);
                    }
                    lg[i] = dot;
                }
                __syncwarp();
                if (lane == 0) mbar_arrive(emptyh + 16 * slot);
                if (++slot == kNS) { slot = 0; ph ^= 1; }
#pragma unroll
                for (int o = 16; o > 0; o >>= 1) {
#pragma unroll
                    for (int i = 0; i < kR; i++) lg[i] += __shfl_xor_sync(0xffffffffu, lg[i], o);
                }
                float mw = -INFINITY;
#pragma unroll
                for (int i = 0; i < kR; i++) {
                    lg[i] = lg[i] * sk[i] * scale_log2e;
                    mw = fmaxf(mw, lg[i]);
                }
                if (lane == 0) {
                    s_max[(it & 3) * kCW + warp] = mw;
                    mbar_arrive(mxbar + 8 * (it & 1));
                }
            }
            if (it > 0) {
                const int r = it - 1;
                float* my = my0 + (r & 1) * (kCW * kScStride);
                const int df = deferred_to(4 * half + m / 8, r);
                const unsigned char* sp = smem + kOffScal + r * (4 * kRows * 2) + warp * (kR * 2);
                const uint2 uvs = *reinterpret_cast<const uint2*>(sp + 2 * kRows * 2);
                const uint2 uvz = *reinterpret_cast<const uint2*>(sp + 3 * kRows * 2);
                const float vz[4] = {bf_lo(uvz.x), bf_hi(uvz.x), bf_lo(uvz.y), bf_hi(uvz.y)};
                const float sv[4] = {bf_lo(uvs.x), bf_hi(uvs.x), bf_lo(uvs.y), bf_hi(uvs.y)};
                mbar_wait(mxbar + 8 * (r & 1), (r >> 1) & 1);
                float M;
                {
                    const float4* pm4 = reinterpret_cast<const float4*>(s_max + (r & 3) * kCW);
                    const float4 m0 = pm4[0], m1 = pm4[1], m2 = pm4[2], m3 = pm4[3];
                    M = fmaxf(fmaxf(fmaxf(fmaxf(m0.x, m0.y), fmaxf(m0.z, m0.w)), fmaxf(fmaxf(m1.x, m1.y), fmaxf(m1.z, m1.w))),
                              fmaxf(fmaxf(fmaxf(m2.x, m2.y), fmaxf(m2.z, m2.w)), fmaxf(fmaxf(m3.x, m3.y), fmaxf(m3.z, m3.w))));
                }
                float lw = 0.f, cz = 0.f, pv[kR];
#pragma unroll
                for (int i = 0; i < kR; i++) {
                    const float p = exp2f(lgc[i] - M);
                    lw += p;
                    pv[i] = p * sv[i];
                    cz = fmaf(pv[i], vz[i], cz);
                }
                mbar_wait(sempty + 8 * (r & 1), ((r >> 1) & 1) ^ 1);
                if (lane == 0) { my[0] = M; my[1] = lw; }
                float acc[6] = {-cz, -cz, -cz, -cz, -cz, -cz};
                if (df < kF) {
                    if (lane < kR)
                        st_ml(g_lg + ((team * kFHeads + r - kDef0) * kF + df) * kFRows + (m % 8) * kHRows + (warp % 8) * kR + lane, M,
                              lane == 0 ? pv[0] : lane == 1 ? pv[1] : lane == 2 ? pv[2] : pv[3], s_misc[0] % 255u + 1u);
                } else {
                    mbar_wait(fullh + 16 * slot, ph);
                    if ((threadIdx.x & 255) < kNP) asm volatile("red.relaxed.gpu.global.add.u32 [%0], 1;" ::"l"(g_prog + lane * 1024) : "memory");
                    const unsigned char* vb = smem + slot * kChunk + warp * (kR * kRowBytes) + lane * 8;
#pragma unroll
                    for (int i = 0; i < kR; i++) {
#pragma unroll
                        for (int j = 0; j < 3; j++) {
                            const int2 vv = *reinterpret_cast<const int2*>(vb + i * kRowBytes + 256 * j);
                            acc[2 * j] = fmaf(pv[i], (float)vv.x, acc[2 * j]);
                            acc[2 * j + 1] = fmaf(pv[i], (float)vv.y, acc[2 * j + 1]);
                        }
                    }
                    __syncwarp();
                    if (lane == 0) mbar_arrive(emptyh + 16 * slot);
                    if (++slot == kNS) { slot = 0; ph ^= 1; }
                }
#pragma unroll
                for (int j = 0; j < 3; j++)
                    *reinterpret_cast<float2*>(my + 4 + 64 * j + 2 * lane) = make_float2(acc[2 * j], acc[2 * j + 1]);
                __syncwarp();
                if (lane == 0) mbar_arrive(sfull + 8 * (r & 1));
            }
#pragma unroll
            for (int i = 0; i < kR; i++) lgc[i] = lg[i];
        }
        {
            const int cp = lane < kFW / 2 ? lane : 0;
            const int ft = threadIdx.x < kFW ? threadIdx.x : 0;
            const float fin = reinterpret_cast<const float*>(smem + kOffFin)[ft];
            __nv_bfloat16* op = out + (size_t)(kTeams * (kDef0 + m / kFG) + team) * kD + (m % kFG) * kFW + ft;
            float a0 = 0.f, a1 = 0.f, b0 = 0.f, b1 = 0.f;
#pragma unroll 1
            for (int f = 0; f < kF; f++) {
                const float* sw = reinterpret_cast<const float*>(smem + kOffW) + f * kFRows + (warp >> 2) * 16 + (warp & 3) * 4;
                const unsigned char* vb = smem + slot * kChunk + ((warp >> 2) * 16 + (warp & 3) * 4) * (kFW * 4) + cp * 8;
                const uint32_t fb = fine + (f * kFBoxes + (warp >> 2)) * 8;
                float* part = reinterpret_cast<float*>(smem + kOffPart) + f * kPartSize;
                float4 w[4];
#pragma unroll
                for (int k = 0; k < 4; k++) w[k] = *reinterpret_cast<const float4*>(sw + 64 * k);
#pragma unroll
                for (int k = 0; k < 4; k++) {
                    mbar_wait(fb + 32 * k, 0);
                    if ((k & 1) && warp == kCW - 1 && lane < kNP && f < kF - 1) asm volatile("red.relaxed.gpu.global.add.u32 [%0], 1;" ::"l"(g_prog + lane * 1024) : "memory");
                    const int2 v0 = *reinterpret_cast<const int2*>(vb + k * (64 * kFW * 4));
                    const int2 v1 = *reinterpret_cast<const int2*>(vb + k * (64 * kFW * 4) + kFW * 4);
                    const int2 v2 = *reinterpret_cast<const int2*>(vb + k * (64 * kFW * 4) + 2 * kFW * 4);
                    const int2 v3 = *reinterpret_cast<const int2*>(vb + k * (64 * kFW * 4) + 3 * kFW * 4);
                    a0 = fmaf(w[k].x, (float)v0.x, a0); a1 = fmaf(w[k].x, (float)v0.y, a1);
                    b0 = fmaf(w[k].y, (float)v1.x, b0); b1 = fmaf(w[k].y, (float)v1.y, b1);
                    a0 = fmaf(w[k].z, (float)v2.x, a0); a1 = fmaf(w[k].z, (float)v2.y, a1);
                    b0 = fmaf(w[k].w, (float)v3.x, b0); b1 = fmaf(w[k].w, (float)v3.y, b1);
                }
                if (lane < kFW / 2) {
                    part[lane * kPartStride + warp] = a0 + b0;
                    part[kPartOdd + lane * kPartStride + warp] = a1 + b1;
                }
                if (warp >= 2) {
                    asm volatile("bar.arrive %0, %1;" ::"r"(3 + f), "n"(kCW * 32) : "memory");
                } else {
                    asm volatile("bar.sync %0, %1;" ::"r"(3 + f), "n"(kCW * 32) : "memory");
                    const float4* ps = reinterpret_cast<const float4*>(part + (ft & 1) * kPartOdd + (ft >> 1) * kPartStride);
                    const float4 p0 = ps[0], p1 = ps[1], p2 = ps[2], p3 = ps[3];
                    const float sum = (((p0.x + p0.y) + (p0.z + p0.w)) + ((p1.x + p1.y) + (p1.z + p1.w))) +
                                      (((p2.x + p2.y) + (p2.z + p2.w)) + ((p3.x + p3.y) + ((p3.z + p3.w) + fin)));
                    asm volatile("{\n.reg .pred p;\n.reg .b16 h;\nsetp.ne.u32 p, %2, 0;\ncvt.rn.bf16.f32 h, %1;\n@p st.global.b16 [%0], h;\n}"
                                 ::"l"(op), "f"(sum), "r"((uint32_t)(f == kF - 1 && threadIdx.x < kFW)) : "memory");
                }
                if (++slot == kNS) slot = 0;
            }
        }
    }
}

__global__ void __launch_bounds__(256)
attn_fallback(const __nv_bfloat16* __restrict__ q, const int* __restrict__ qk,
              const __nv_bfloat16* __restrict__ ksc, const __nv_bfloat16* __restrict__ kzp,
              const int* __restrict__ qv, const __nv_bfloat16* __restrict__ vsc,
              const __nv_bfloat16* __restrict__ vzp, const __nv_bfloat16* __restrict__ qcos,
              const __nv_bfloat16* __restrict__ qsin, const __nv_bfloat16* __restrict__ kcos,
              const __nv_bfloat16* __restrict__ ksin, __nv_bfloat16* __restrict__ out) {
    __shared__ float qr[kD], lg[kS], red[8];
    const int h = blockIdx.x, t = threadIdx.x, warp = t >> 5, lane = t & 31;
    if (t < kD) {
        const float x = __bfloat162float(q[h * kD + t]);
        const float y = t < kD / 2 ? -__bfloat162float(q[h * kD + t + kD / 2]) : __bfloat162float(q[h * kD + t - kD / 2]);
        qr[t] = bf_round(bf_round(x * __bfloat162float(qcos[t])) + bf_round(y * __bfloat162float(qsin[t])));
    }
    __syncthreads();
    const float scale_log2e = 1.4426950408889634f * rsqrtf((float)kD);
    float mw = -INFINITY;
    for (int s = warp; s < kS; s += 8) {
        const size_t row = (size_t)h * kS + s;
        const float z = __bfloat162float(kzp[row]);
        float dot = 0.f;
        for (int d = lane; d < kD; d += 32) {
            const int dp = d < kD / 2 ? d + kD / 2 : d - kD / 2;
            const float sn = __bfloat162float(ksin[s * kD + dp]);
            const float e = qr[d] * __bfloat162float(kcos[s * kD + d]) + qr[dp] * (d < kD / 2 ? sn : -sn);
            dot = fmaf((float)qk[row * kD + d] - z, e, dot);
        }
        for (int o = 16; o > 0; o >>= 1) dot += __shfl_xor_sync(0xffffffffu, dot, o);
        dot = dot * __bfloat162float(ksc[row]) * scale_log2e;
        if (lane == 0) lg[s] = dot;
        mw = fmaxf(mw, dot);
    }
    if (lane == 0) red[warp] = mw;
    __syncthreads();
    float M = red[0];
    for (int i = 1; i < 8; i++) M = fmaxf(M, red[i]);
    __syncthreads();
    float l = 0.f;
    for (int s = t; s < kS; s += 256) { const float p = exp2f(lg[s] - M); l += p; lg[s] = p; }
    for (int o = 16; o > 0; o >>= 1) l += __shfl_xor_sync(0xffffffffu, l, o);
    if (lane == 0) red[warp] = l;
    __syncthreads();
    float L = 0.f;
    for (int i = 0; i < 8; i++) L += red[i];
    if (t < kD) {
        float acc = 0.f;
        for (int s = 0; s < kS; s++) {
            const size_t row = (size_t)h * kS + s;
            acc = fmaf(lg[s] * __bfloat162float(vsc[row]), (float)qv[row * kD + t] - __bfloat162float(vzp[row]), acc);
        }
        out[h * kD + t] = __float2bfloat16_rn(acc / L);
    }
}

}

extern "C" void kernel_launch(void* const* d_in, const int* in_sizes, int n_in, void* d_out, int out_size) {
    const __nv_bfloat16* q = (const __nv_bfloat16*)d_in[0];
    const int* qk = (const int*)d_in[1];
    const __nv_bfloat16* ksc = (const __nv_bfloat16*)d_in[2];
    const __nv_bfloat16* kzp = (const __nv_bfloat16*)d_in[3];
    const int* qv = (const int*)d_in[4];
    const __nv_bfloat16* vsc = (const __nv_bfloat16*)d_in[5];
    const __nv_bfloat16* vzp = (const __nv_bfloat16*)d_in[6];
    const __nv_bfloat16* qcos = (const __nv_bfloat16*)d_in[7];
    const __nv_bfloat16* qsin = (const __nv_bfloat16*)d_in[8];
    const __nv_bfloat16* kcos = (const __nv_bfloat16*)d_in[9];
    const __nv_bfloat16* ksin = (const __nv_bfloat16*)d_in[10];

    typedef CUresult (*EncodeFn)(CUtensorMap*, CUtensorMapDataType, cuuint32_t, void*, const cuuint64_t*, const cuuint64_t*,
                                 const cuuint32_t*, const cuuint32_t*, CUtensorMapInterleave, CUtensorMapSwizzle,
                                 CUtensorMapL2promotion, CUtensorMapFloatOOBfill);
    static EncodeFn encode = nullptr;
    static int by_sm = 0;
    static int mode = 0;
    if (!mode) {
        int dev = 0, sms = 0, occ = 0;
        cudaGetDevice(&dev);
        cudaDeviceGetAttribute(&sms, cudaDevAttrMultiProcessorCount, dev);
        cudaError_t e = cudaFuncSetAttribute(attn_kernel, cudaFuncAttributeMaxDynamicSharedMemorySize, kSmemBytes);
        if (e == cudaSuccess) e = cudaOccupancyMaxActiveBlocksPerMultiprocessor(&occ, attn_kernel, kThreads, kSmemBytes);
        void* fn = nullptr;
        cudaDriverEntryPointQueryResult qr;
        if (e == cudaSuccess) e = cudaGetDriverEntryPoint("cuTensorMapEncodeTiled", &fn, cudaEnableDefault, &qr);
        encode = (EncodeFn)fn;
        mode = (e == cudaSuccess && fn && occ * sms >= kGrid) ? 1 : 2;
        (void)cudaGetLastError();
        by_sm = sms == kGrid && occ == 1;
    }
    CUtensorMap tmv;
    bool fast = mode == 1;
    if (fast) {
        const cuuint64_t dims[2] = {(cuuint64_t)kD, (cuuint64_t)kNH * kS}, strides[1] = {(cuuint64_t)kRowBytes};
        const cuuint32_t box[2] = {(cuuint32_t)kFW, (cuuint32_t)(kFRows / kFBoxes)}, es[2] = {1, 1};
        fast = encode(&tmv, CU_TENSOR_MAP_DATA_TYPE_INT32, 2, (void*)qv, dims, strides, box, es, CU_TENSOR_MAP_INTERLEAVE_NONE,
                      CU_TENSOR_MAP_SWIZZLE_NONE, CU_TENSOR_MAP_L2_PROMOTION_L2_128B, CU_TENSOR_MAP_FLOAT_OOB_FILL_NONE) == CUDA_SUCCESS;
    }
    if (fast)
        attn_kernel<<<kGrid, kThreads, kSmemBytes>>>(Scalars{{ksc, kzp, vsc, vzp}}, qk, by_sm, kcos, ksin, qv, q, qcos, qsin,
                                                     (__nv_bfloat16*)d_out, tmv);
    else
        attn_fallback<<<kNH, 256>>>(q, qk, ksc, kzp, qv, vsc, vzp, qcos, qsin, kcos, ksin, (__nv_bfloat16*)d_out);
}
```

```cpp
#include <cuda_runtime.h>
#include <cuda.h>
#include <cuda_bf16.h>
#include <stdint.h>

namespace {

constexpr int kB = 8, kH = 32, kS = 2048, kD = 192;
constexpr int kNH = kB * kH;
constexpr int kTeams = 4;
constexpr int kSlots = 32;
constexpr int kRows = kS / kSlots;
constexpr int kRounds = kNH / kTeams;
constexpr int kStream = kTeams * kSlots;
constexpr int kGrid = kStream + kTeams;
constexpr int kCW = 16;
constexpr int kR = kRows / kCW;
constexpr int kNP = 2;
constexpr int kThreads = (kCW + 2 + kNP) * 32;
constexpr int kRowBytes = kD * 4;
constexpr int kChunk = kRows * kRowBytes;
constexpr int kNS = 3;
constexpr int kHalf = kChunk / 2;
constexpr int kHRows = kRows / 2;
constexpr int kLead = 240;
constexpr int kLeadEnd = 215;
constexpr int kRampEnd = 12, kRampStep = 70;
constexpr int kWaveSlot = 2, kWaveHalf = 48, kWaveV = 16, kWaveRamp = 8;
constexpr uint32_t kRate = 69, kAhead = 256;
constexpr int kPollSleep = 300;
constexpr int kQuick = 20;
constexpr int kSleep = 200;
constexpr int kPR = 12;
constexpr int kScStride = 196;
constexpr int kOffScal = kNS * kChunk;
constexpr int kOffQ = kOffScal + kRounds * 4 * kRows * 2;
constexpr int kOffSc = kOffQ + kRounds * kD * 2;
constexpr int kOffBar = kOffSc + 2 * kCW * kScStride * 4;
constexpr int kF = 3;
constexpr int kFG = 4;
constexpr int kFW = kD / kFG;
constexpr int kFRows = kRows * kFG;
constexpr int kFHeads = kSlots / kFG;
constexpr int kDef0 = 16;
constexpr int kEarly = 4;
constexpr int kFBoxes = 16;
constexpr int kPrep = 40;
constexpr int kOffW = kOffScal;
constexpr int kOffFin = kOffW + kF * kFRows * 4;
constexpr int kPartStride = 20, kPartOdd = (kFW / 2) * kPartStride + 16, kPartSize = 2 * kPartOdd;
constexpr int kOffPart = kOffFin + kFW * 4;
constexpr int kOffMisc = kOffBar + (4 * kNS + 6 + kF * kFBoxes) * 8;
constexpr int kOffMax = kOffMisc + 32;
constexpr int kSmemBytes = kOffMax + 4 * kCW * 4;
constexpr int kRecWords = 112;
constexpr int kMG = 6;
static_assert(kNS >= 3, "ring");
static_assert(kOffBar % 8 == 0 && kOffSc % 16 == 0 && kOffMax % 16 == 0, "alignment");
static_assert(kPR % kMG == 0, "ring");
static_assert(kNP == 2 && kOffMisc % 16 == 0 && kLeadEnd >= kStream && kS == kFHeads * kFRows && kFHeads == 8, "schedule");
static_assert(kSmemBytes <= 232448, "smem");
static_assert(kDef0 + kFHeads < kPrep && kPrep + 16 + 3 < kRounds && kEarly + kF * kFBoxes + 3 < kRounds && kOffPart <= kOffScal + (kPrep - 2) * 4 * kRows * 2 &&
              kOffPart + kF * kPartSize * 4 <= kOffScal + (kRounds - 2) * 4 * kRows * 2 && kF <= kNS && kFBoxes == kCW, "deferred rounds");

__device__ __align__(128) unsigned long long g_rec[kPR * kStream * kRecWords];
__device__ __align__(128) unsigned long long g_pre[kTeams * kFHeads * kRecWords];
__device__ __align__(128) unsigned long long g_lg[kTeams * kFHeads * kF * kFRows];
__device__ __align__(8192) unsigned int g_prog[kNP * 1024];
__device__ __align__(128) unsigned int g_epoch;
__device__ __align__(128) unsigned int g_arrive;
__device__ __align__(128) unsigned int g_mdone[kTeams * kMG * 32];

constexpr int kSpin = 1 << 24;

__device__ __forceinline__ uint32_t clock32() {
    uint32_t t;
    asm volatile("mov.u32 %0, %%clock;" : "=r"(t)::"memory");
    return t;
}
__device__ __forceinline__ uint32_t s2u(const void* p) { return (uint32_t)__cvta_generic_to_shared(p); }
__device__ __forceinline__ void mbar_init(uint32_t a, int c) {
    asm volatile("mbarrier.init.shared::cta.b64 [%0], %1;" ::"r"(a), "r"(c));
}
__device__ __forceinline__ void mbar_wait(uint32_t a, uint32_t ph) {
    uint32_t ok;
    for (int it = 0;; it++) {
        asm volatile(
            "{\n.reg .pred p;\nmbarrier.try_wait.parity.shared::cta.b64 p, [%1], %2;\nselp.u32 %0, 1, 0, p;\n}"
            : "=r"(ok) : "r"(a), "r"(ph) : "memory");
        if (ok) break;
        if (it > kSpin) __trap();
    }
}
__device__ __forceinline__ void mbar_arrive(uint32_t a) {
    asm volatile("mbarrier.arrive.shared::cta.b64 _, [%0];" ::"r"(a) : "memory");
}
__device__ __forceinline__ void mbar_expect(uint32_t a, uint32_t bytes) {
    asm volatile("mbarrier.arrive.expect_tx.shared::cta.b64 _, [%0], %1;" ::"r"(a), "r"(bytes) : "memory");
}
__device__ __forceinline__ void bulk_g2s_stream(uint32_t dst, const void* src, uint32_t bytes, uint32_t mbar, uint64_t pol) {
    asm volatile("cp.async.bulk.shared::cluster.global.mbarrier::complete_tx::bytes.L2::cache_hint [%0], [%1], %2, [%3], %4;"
                 ::"r"(dst), "l"(src), "r"(bytes), "r"(mbar), "l"(pol) : "memory");
}
__device__ __forceinline__ void bulk_g2s(uint32_t dst, const void* src, uint32_t bytes, uint32_t mbar) {
    asm volatile("cp.async.bulk.shared::cluster.global.mbarrier::complete_tx::bytes [%0], [%1], %2, [%3];"
                 ::"r"(dst), "l"(src), "r"(bytes), "r"(mbar) : "memory");
}
__device__ __forceinline__ void cp16(uint32_t dst, const void* src) {
    asm volatile("cp.async.cg.shared.global [%0], [%1], 16;" ::"r"(dst), "l"(src) : "memory");
}
__device__ __forceinline__ float bf_lo(uint32_t u) { return __uint_as_float(u << 16); }
__device__ __forceinline__ float bf_hi(uint32_t u) { return __uint_as_float(u & 0xffff0000u); }
__device__ __forceinline__ float bf_round(float x) { return __bfloat162float(__float2bfloat16_rn(x)); }
__device__ __forceinline__ uint32_t ld_pair(const __nv_bfloat16* p) {
    return __ldg(reinterpret_cast<const uint32_t*>(p));
}
__device__ __forceinline__ unsigned int ld_relaxed(const unsigned int* p) {
    unsigned int v;
    asm volatile("ld.relaxed.gpu.global.u32 %0, [%1];" : "=r"(v) : "l"(p) : "memory");
    return v;
}
__device__ __forceinline__ unsigned long long pack_rec(float a, float b, uint32_t tag) {
    const uint32_t x = (__float_as_uint(a) & ~15u) | (tag & 15u), y = (__float_as_uint(b) & ~15u) | (tag >> 4);
    return ((unsigned long long)y << 32) | x;
}
__device__ __forceinline__ void st_rec(unsigned long long* p, float a, float b, uint32_t tag) {
    asm volatile("st.relaxed.gpu.global.b64 [%0], %1;" ::"l"(p), "l"(pack_rec(a, b, tag)) : "memory");
}
__device__ __forceinline__ float rec_lo(unsigned long long w) { return __uint_as_float((uint32_t)w & ~15u); }
__device__ __forceinline__ float rec_hi(unsigned long long w) { return __uint_as_float((uint32_t)(w >> 32) & ~15u); }
__device__ __forceinline__ unsigned long long ld_rec1(const unsigned long long* p) {
    unsigned long long x;
    asm volatile("ld.relaxed.gpu.global.b64 %0, [%1];" : "=l"(x) : "l"(p) : "memory");
    return x;
}
__device__ __forceinline__ void ld_rec2(const unsigned long long* p, unsigned long long& x, unsigned long long& y) {
    asm volatile("ld.relaxed.gpu.global.v2.b64 {%0, %1}, [%2];" : "=l"(x), "=l"(y) : "l"(p) : "memory");
}
__device__ __forceinline__ uint32_t rec_bad(unsigned long long w, uint32_t tlo, uint32_t thi) {
    return (((uint32_t)w ^ tlo) | ((uint32_t)(w >> 32) ^ thi)) & 15u;
}
__device__ __forceinline__ void st_ml(unsigned long long* p, float m, float l, uint32_t tag) {
    const uint32_t y = ((__float_as_uint(l) + 0x80u) & ~0xffu) | tag;
    asm volatile("st.relaxed.gpu.global.b64 [%0], %1;" ::"l"(p), "l"(((unsigned long long)y << 32) | __float_as_uint(m)) : "memory");
}
__device__ __forceinline__ uint32_t ml_bad(unsigned long long w, uint32_t tag) { return ((uint32_t)(w >> 32) ^ tag) & 0xffu; }
__device__ __forceinline__ float ml_m(unsigned long long w) { return __uint_as_float((uint32_t)w); }
__device__ __forceinline__ float ml_l(unsigned long long w) { return __uint_as_float((uint32_t)(w >> 32) & ~0xffu); }
__device__ __forceinline__ float warp_max(float v) {
    const int b = __float_as_int(v);
    const int k = __reduce_max_sync(0xffffffffu, b ^ ((b >> 31) & 0x7fffffff));
    return __int_as_float(k ^ ((k >> 31) & 0x7fffffff));
}
__device__ __forceinline__ uint32_t round_tag(unsigned int epoch, int r) {
    constexpr unsigned kUses = (kRounds + kPR - 1) / kPR;
    return (epoch * kUses + (unsigned)(r / kPR)) % 255u + 1u;
}

__device__ __forceinline__ void rotate_q(uint32_t* qrow, int p, uint32_t c_lo, uint32_t c_hi, uint32_t s_lo, uint32_t s_hi) {
    const uint32_t lo = qrow[p], hi = qrow[p + 48];
    const float a0 = bf_round(bf_lo(lo) * bf_lo(c_lo)) + bf_round(-bf_lo(hi) * bf_lo(s_lo));
    const float a1 = bf_round(bf_hi(lo) * bf_hi(c_lo)) + bf_round(-bf_hi(hi) * bf_hi(s_lo));
    const float b0 = bf_round(bf_lo(hi) * bf_lo(c_hi)) + bf_round(bf_lo(lo) * bf_lo(s_hi));
    const float b1 = bf_round(bf_hi(hi) * bf_hi(c_hi)) + bf_round(bf_hi(lo) * bf_hi(s_hi));
    const __nv_bfloat162 ua = __floats2bfloat162_rn(a0, a1), ub = __floats2bfloat162_rn(b0, b1);
    qrow[p] = *reinterpret_cast<const uint32_t*>(&ua);
    qrow[p + 48] = *reinterpret_cast<const uint32_t*>(&ub);
}
__device__ __forceinline__ int deferred_to(int blk, int r) {
    return (unsigned)(r - kDef0) < (unsigned)kFHeads ? (blk - kF * (r - kDef0)) & (kFHeads - 1) : kF;
}

__device__ __forceinline__ unsigned role_of_sm(unsigned smid) {
    const unsigned u = smid >> 1;
    const unsigned g = u < 32 ? u & 7 : u < 60 ? 1 + (u - 32) % 7 : u < 62 ? u - 54 : 0;
    const unsigned t = u < 32 ? u >> 3 : u < 60 ? 4 + (u - 32) / 7 : u < 62 ? 8 : u - 58;
    const unsigned lin = 16 * g + (g == 7 ? 2 : 0) + 2 * t + (smid & 1);
    if (lin < 2 || lin == 48 || lin == 49) return kStream + (lin & 1) + (lin < 2 ? 0 : 2);
    const unsigned x = lin - (lin < 48 ? 2 : 4);
    return (x & 14) * 8 + (x >> 4) * 2 + (x & 1);
}
static_assert(kGrid == 132 && kTeams == 4, "role_of_sm");
struct Scalars { const __nv_bfloat16* p[4]; };

__global__ void __launch_bounds__(kThreads, 1)
attn_kernel(const __grid_constant__ Scalars scal, const int* __restrict__ qk, int by_sm, const __nv_bfloat16* __restrict__ kcos,
            const __nv_bfloat16* __restrict__ ksin, const int* __restrict__ qv, const __nv_bfloat16* __restrict__ q,
            const __nv_bfloat16* __restrict__ qcos, const __nv_bfloat16* __restrict__ qsin,
            __nv_bfloat16* __restrict__ out, const __grid_constant__ CUtensorMap tmv) {
    extern __shared__ __align__(128) unsigned char smem[];
    const int warp = threadIdx.x >> 5, lane = threadIdx.x & 31;
    const uint32_t full0 = s2u(smem + kOffBar), empty0 = full0 + 2 * kNS * 8;
    const uint32_t sfull = empty0 + 2 * kNS * 8, sempty = sfull + 16, mxbar = sempty + 16, fine = mxbar + 16;
    volatile unsigned int* s_misc = reinterpret_cast<volatile unsigned int*>(smem + kOffMisc);
    uint64_t pol = 0;

    asm volatile("prefetch.global.L2 [%0];"
                 ::"l"(reinterpret_cast<const char*>(qk) + (blockIdx.x * (kThreads / 4) + threadIdx.x / 4) * 128) : "memory");
    unsigned bid = blockIdx.x;
    if (by_sm) {
        unsigned smid, nsm;
        asm volatile("mov.u32 %0, %%smid;" : "=r"(smid));
        asm volatile("mov.u32 %0, %%nsmid;" : "=r"(nsm));
        if (nsm == kGrid) bid = role_of_sm(smid);
    }
    if (threadIdx.x == kCW * 32 && bid < kStream) {
        const int m = bid % kSlots;
        const uint32_t sm0 = s2u(smem);
        asm volatile("cp.async.bulk.prefetch.L2.global [%0], %1;"
                     ::"l"(scal.p[bid & 3] + (bid >> 2) * (kNH * kS * 4 / kStream)), "n"(kNH * kS * 4 / kStream * 2) : "memory");
        for (int i = 0; i < 2 * kNS; i++) mbar_init(full0 + 8 * i, 1);
        asm volatile("fence.mbarrier_init.release.cluster;" ::: "memory");
        asm volatile("createpolicy.fractional.L2::evict_first.b64 %0, 1.0;" : "=l"(pol));
        const int* k0 = qk + (size_t)(bid / kSlots * kS + m * kHRows) * kD;
#pragma unroll
        for (int h = 0; h < 2; h++) {
            mbar_expect(full0 + 16 + 8 * h, kHalf);
            bulk_g2s_stream(sm0 + kChunk + h * kHalf, k0 + h * (kS / 2 * kD), kHalf, full0 + 16 + 8 * h, pol);
        }
#pragma unroll
        for (int h = 0; h < 2; h++) {
            mbar_expect(full0 + 8 * h, kHalf);
            bulk_g2s(sm0 + h * kHalf, kcos + (h * (kS / 2) + m * kHRows) * kD, kHalf / 2, full0 + 8 * h);
            bulk_g2s(sm0 + h * kHalf + kHalf / 2, ksin + (h * (kS / 2) + m * kHRows) * kD, kHalf / 2, full0 + 8 * h);
        }
#pragma unroll
        for (int h = 0; h < 2; h++) {
            mbar_expect(full0 + 32 + 8 * h, kHalf);
            bulk_g2s_stream(sm0 + 2 * kChunk + h * kHalf, k0 + (kTeams * kS + h * (kS / 2)) * kD, kHalf, full0 + 32 + 8 * h, pol);
        }
    }

    if (bid >= kStream) {
        const int team = bid - kStream;
        if (threadIdx.x == 0) s_misc[0] = ld_relaxed(&g_epoch);
        __syncthreads();
        if (threadIdx.x == 0 && atomicAdd(&g_arrive, 1u) == kGrid - 1) { g_arrive = 0u; g_epoch = s_misc[0] + 1u; }
        if (warp >= 3 * kMG) return;
        const int grp = warp / 3, t = threadIdx.x - grp * 96;
        constexpr int kRecBytes = kSlots * kRecWords * 8;
        if (t == 0) {
            mbar_init(s2u(smem + kOffBar) + grp * 8, 1);
            asm volatile("fence.mbarrier_init.release.cluster;" ::: "memory");
        }
        asm volatile("bar.sync %0, 96;" ::"r"(3 + grp) : "memory");
        for (int r = grp; r < kRounds; r += kMG) {
            const int g = r % kMG;
            const int tt = threadIdx.x - g * 96, qd = tt % 48, half = tt / 48;
            const uint32_t tag = round_tag(s_misc[0], r);
            const uint32_t tlo = tag & 15u, thi = tag >> 4;
            const unsigned long long* rec = g_rec + ((size_t)(r % kPR) * kStream + team * kSlots) * kRecWords;
            unsigned long long ml, x[16], y[16];
            {
                const unsigned long long* buf = reinterpret_cast<const unsigned long long*>(smem + g * kRecBytes);
                const uint32_t mb = s2u(smem + kOffBar) + g * 8;
                if (tt < 32) {
                    const int want = r == kRounds - 1 ? kQuick : kSlots;
                    for (int i2 = 0;; i2++) {
                        ml = ld_rec1(rec + lane * kRecWords + 96);
                        if (__popc(__ballot_sync(0xffffffffu, ml_bad(ml, tag) == 0)) >= want) break;
                        if (i2 > kSpin) __trap();
                        __nanosleep(kSleep);
                    }
                    if (tt == 0) {
                        mbar_expect(mb, kRecBytes);
                        bulk_g2s(s2u(buf), rec, kRecBytes, mb);
                    }
                }
                mbar_wait(mb, (r / kMG) & 1);
                ml = buf[lane * kRecWords + 96];
#pragma unroll
                for (int i = 0; i < 16; i++) {
                    const ulonglong2 u = *reinterpret_cast<const ulonglong2*>(buf + (half * 16 + i) * kRecWords + 2 * qd);
                    x[i] = u.x; y[i] = u.y;
                }
                const unsigned long long* po = rec + half * 16 * kRecWords + 2 * qd;
                for (int it = 0;; it++) {
                    uint32_t any = ml_bad(ml, tag);
                    if (any) ml = ld_rec1(rec + lane * kRecWords + 96);
#pragma unroll
                    for (int i = 0; i < 16; i++) {
                        const uint32_t bad = rec_bad(x[i], tlo, thi) | rec_bad(y[i], tlo, thi);
                        if (bad) ld_rec2(po + i * kRecWords, x[i], y[i]);
                        any |= bad;
                    }
                    if (__all_sync(0xffffffffu, any == 0)) break;
                    if (it > kSpin) __trap();
                }
            }
            const float M = ml_m(ml);
            const float MM = warp_max(M);
            const float w = exp2f(M - MM);
            float LL = w * ml_l(ml);
#pragma unroll
            for (int o = 16; o > 0; o >>= 1) LL += __shfl_xor_sync(0xffffffffu, LL, o);
            float4 a = make_float4(0.f, 0.f, 0.f, 0.f);
#pragma unroll
            for (int i = 0; i < 16; i++) {
                const float wi = __shfl_sync(0xffffffffu, w, half * 16 + i);
                a.x = fmaf(wi, rec_lo(x[i]), a.x);
                a.y = fmaf(wi, rec_hi(x[i]), a.y);
                a.z = fmaf(wi, rec_lo(y[i]), a.z);
                a.w = fmaf(wi, rec_hi(y[i]), a.w);
            }
            float* rb = reinterpret_cast<float*>(smem + kMG * kRecBytes) + (2 * g + ((r / kMG) & 1)) * kD + 4 * qd;
            if (half == 1) *reinterpret_cast<float4*>(rb) = a;
            asm volatile("bar.sync %0, 96;" ::"r"(3 + g) : "memory");
            if (half == 0) {
                const float4 u = *reinterpret_cast<float4*>(rb);
                if ((unsigned)(r - kDef0) < (unsigned)kFHeads) {
                    unsigned long long* pre = g_pre + (size_t)(team * kFHeads + r - kDef0) * kRecWords;
                    const uint32_t ptag = s_misc[0] % 255u + 1u;
                    st_rec(pre + 2 * qd, a.x + u.x, a.y + u.y, ptag);
                    st_rec(pre + 2 * qd + 1, a.z + u.z, a.w + u.w, ptag);
                    if (qd == 0) st_ml(pre + 96, MM, LL, ptag);
                } else {
                    const float inv = __fdividef(1.0f, LL);
                    const __nv_bfloat162 o0 = __floats2bfloat162_rn((a.x + u.x) * inv, (a.y + u.y) * inv);
                    const __nv_bfloat162 o1 = __floats2bfloat162_rn((a.z + u.z) * inv, (a.w + u.w) * inv);
                    uint2 ov;
                    ov.x = *reinterpret_cast<const uint32_t*>(&o0);
                    ov.y = *reinterpret_cast<const uint32_t*>(&o1);
                    *reinterpret_cast<uint2*>(out + (size_t)(kTeams * r + team) * kD + 4 * qd) = ov;
                }
            }
            if (tt == 95)
                asm volatile("st.relaxed.gpu.global.u32 [%0], %1;" ::"l"(&g_mdone[(team * kMG + g) * 32]), "r"(s_misc[0] * kRounds + r + 1) : "memory");
        }
        return;
    }

    const int m = bid % kSlots, team = bid / kSlots;
    const int row0 = m * kHRows;

    if (warp == kCW) {
        unsigned int epoch = 0;
        const size_t off0 = ((size_t)team * kS + row0) * kD;
        const uint32_t sm0 = s2u(smem);
        if (lane == 0) {
            epoch = ld_relaxed(&g_epoch);
            s_misc[0] = epoch;
            s_misc[1] = 0;
            for (int j = 0; j < kNP; j++) {
                s_misc[4 + 2 * j] = epoch * (kStream * (4 * kRounds - 2));
                s_misc[5 + 2 * j] = clock32();
            }
        }
        __syncwarp();
        asm volatile("bar.sync 2, %0;" ::"n"(kThreads) : "memory");
        if (lane == 0) {
            const unsigned int base = epoch * (kStream * (4 * kRounds - 2));
            const int phase = (2 * team - (kTeams - 1)) * (kStream / 2) + (m - kSlots / 2) * kWaveSlot;
            int use0 = kNS, use1 = kNS;
            const int* kp = qk + off0;
            const int* vp = qv + off0;
            for (int ph2 = 4; ph2 < 2 * (2 * kRounds + kF); ph2++) {
                const int p = ph2 >> 1, h = ph2 & 1;
                const bool isv = (p & 1) == 0 || p == 2 * kRounds - 1;
                const int r = p == 2 * kRounds - 1 ? kRounds - 1 : isv ? (p >> 1) - 1 : (p + 1) >> 1;
                const int ramp = max(min(min(ph2 - 4, 4 * kRounds - ph2), kWaveRamp), 0);
                const int tau = kStream * ph2 + (phase + (h ? -kWaveHalf : kWaveHalf) + (isv ? kWaveV : -kWaveV)) * ramp / kWaveRamp;
                const int gone = min(max(tau - kStream * (4 * kDef0 + 3), 0), 4 * kStream * kFHeads) * kF / (2 * kFHeads);
                const unsigned int need = base + tau - gone - max(kRampEnd - ph2, 0) * kRampStep - (p >= 2 * kRounds ? kLeadEnd : kLead);
                const bool skip = isv && deferred_to(4 * h + m / 8, r) < kF;
                const int u = h ? use1 : use0;
                const int slot = u >= kNS ? u - kNS : u;
                const uint32_t dst = sm0 + slot * kChunk + h * kHalf, fullb = full0 + 16 * slot + 8 * h;
                const int* src = (isv ? vp : kp) + (size_t)(r * kTeams * kS + h * (kS / 2)) * kD;
                if (!skip) {
                    const int un = u + 1 == 2 * kNS ? 0 : u + 1;
                    if (h) use1 = un; else use0 = un;
                    mbar_wait(fullb + 2 * kNS * 8, u >= kNS ? 0 : 1);
                    if (p < 2 * kRounds) mbar_expect(fullb, kHalf);
                }
                asm volatile("" ::"l"(src), "r"(dst) : "memory");
                if (!skip)
                    for (int it = 0;; it++) {
                        uint32_t x, tx, y, ty;
                        asm volatile("ld.volatile.shared.v4.u32 {%0, %1, %2, %3}, [%4];"
                                     : "=r"(x), "=r"(tx), "=r"(y), "=r"(ty) : "r"(sm0 + kOffMisc + 16) : "memory");
                        const uint32_t now = clock32();
                        x += min(((now - tx) * kRate) >> 10, kAhead);
                        y += min(((now - ty) * kRate) >> 10, kAhead);
                        if ((int)((x - need) & (y - need)) >= 0) break;
                        if (it > 16 * kSpin) __trap();
                    }
                if (ph2 == 2 * (2 * kRounds + kF) - 1) s_misc[1] = 1;
                if (p >= 2 * kRounds || skip) {
                    const int hi = m / kFG;
                    const int row = (kTeams * (kDef0 + hi) + team) * kS + ((kF * hi + p - 2 * kRounds) & (kFHeads - 1)) * kFRows + h * (kFRows / 2);
                    const uint32_t fb = fine + 8 * (kFBoxes / 2) * (ph2 - 4 * kRounds);
#pragma unroll 1
                    for (int w = 0; w < kFBoxes / 2; w++)
                        asm volatile("{\n.reg .pred p;\nsetp.ne.u32 p, %6, 0;\n"
                                     "@p cp.async.bulk.tensor.2d.shared::cluster.global.tile.mbarrier::complete_tx::bytes.L2::cache_hint [%0], [%1, {%2, %3}], [%4], %5;\n}"
                                     ::"r"(dst + w * (kChunk / kFBoxes)), "l"(&tmv), "r"((m % kFG) * kFW), "r"(row + w * (kFRows / kFBoxes)),
                                       "r"(fb + 8 * w), "l"(pol), "r"((uint32_t)!skip) : "memory");
                } else {
                    bulk_g2s_stream(dst, src, kHalf, fullb, pol);
                }
            }
        }
    } else if (warp >= kCW + 2) {
        asm volatile("bar.sync 2, %0;" ::"n"(kThreads) : "memory");
        if (lane == 0) {
            const int j = warp - (kCW + 2);
            for (int it = 0; !s_misc[1]; it++) {
                const uint32_t t = clock32();
                const uint32_t v = ld_relaxed(g_prog + j * 1024);
                asm volatile("st.volatile.shared.v2.u32 [%0], {%1, %2};" ::"r"(s2u(smem) + kOffMisc + 16 + 8 * j), "r"(v), "r"(t) : "memory");
                if (s_misc[1]) break;
                if (it > kSpin) __trap();
                __nanosleep(kPollSleep);
            }
        }
    } else if (warp == kCW + 1) {
        {
            if (lane < 2 * kNS + 6) mbar_init(empty0 + 8 * lane, lane < 2 * kNS ? kCW / 2 : (lane >= 2 * kNS + 2 && lane < 2 * kNS + 4) ? 1 : kCW);
            asm volatile("fence.mbarrier_init.release.cluster;" ::: "memory");
        }
        asm volatile("bar.sync 2, %0;" ::"n"(kThreads) : "memory");
        const unsigned int epoch = s_misc[0];
        if (lane == 0 && atomicAdd(&g_arrive, 1u) == kGrid - 1) { g_arrive = 0u; g_epoch = epoch + 1u; }
        {
            const uint32_t sm0 = s2u(smem);
            const __nv_bfloat16* src = scal.p[lane >> 3] + (size_t)team * kS + row0 + (lane & 4) * (kS / 8) + (lane & 3) * 8;
            const __nv_bfloat16* qs = q + team * kD + lane * 8;
#pragma unroll 1
            for (int r = kEarly; r < kRounds; r++) {
                cp16(sm0 + kOffScal + r * 512 + lane * 16, src + (size_t)r * (kTeams * kS));
                if (lane < 24) cp16(sm0 + kOffQ + r * (kD * 2) + lane * 16, qs + r * (kTeams * kD));
                if (r == 2 * kEarly - 1 || r == kRounds - 1) asm volatile("cp.async.commit_group;" ::: "memory");
            }
        }
        uint32_t cs[2][4];
#pragma unroll
        for (int i = 0; i < 2; i++) {
            const int p = (lane + 32 * i) % 48;
            cs[i][0] = ld_pair(qcos + 2 * p); cs[i][1] = ld_pair(qcos + 2 * p + 96);
            cs[i][2] = ld_pair(qsin + 2 * p); cs[i][3] = ld_pair(qsin + 2 * p + 96);
        }
        asm volatile("cp.async.wait_group 1;" ::: "memory");
        __syncwarp();
        for (int r = 0; r < kRounds; r++) {
            const float* sc = reinterpret_cast<const float*>(smem + kOffSc) + (r & 1) * (kCW * kScStride);
            const uint32_t tag = round_tag(epoch, r);
            unsigned long long* rec = g_rec + ((size_t)(r % kPR) * kStream + team * kSlots + m) * kRecWords;
            if (r >= kEarly && r < kEarly + kF * kFBoxes && lane == 0) {
                mbar_init(fine + 8 * (r - kEarly), 1);
                asm volatile("fence.mbarrier_init.release.cluster;" ::: "memory");
                mbar_expect(fine + 8 * (r - kEarly), kChunk / kFBoxes);
                asm volatile("fence.proxy.async.shared::cta;" ::: "memory");
            }
            if (r == kPrep + m / 2) {
                const unsigned long long* pre = g_pre + (size_t)(team * kFHeads + m / kFG) * kRecWords;
                const unsigned long long* lgp = g_lg + (size_t)(team * kFHeads + m / kFG) * (kF * kFRows);
                const uint32_t ptag = epoch % 255u + 1u;
                unsigned long long ml, po;
                for (int it = 0;; it++) {
                    ml = ld_rec1(pre + 96);
                    po = ld_rec1(pre + (m % kFG) * (kFW / 2) + lane % (kFW / 2));
                    if (!(ml_bad(ml, ptag) | rec_bad(po, ptag & 15u, ptag >> 4))) break;
                    if (it > kSpin) __trap();
                }
                const float inv = 1.0f / ml_l(ml);
                if (lane < kFW / 2) {
                    reinterpret_cast<float2*>(smem + kOffFin)[lane] = make_float2(rec_lo(po) * inv, rec_hi(po) * inv);
                }
#pragma unroll 1
                for (int c = 0; c < kF; c++) {
                    unsigned long long u[8];
                    for (int it = 0;; it++) {
                        uint32_t bad = 0;
#pragma unroll
                        for (int k = 0; k < 8; k++) {
                            u[k] = ld_rec1(lgp + c * kFRows + 32 * k + lane);
                            bad |= ml_bad(u[k], ptag);
                        }
                        if (!bad) break;
                        if (it > kSpin) __trap();
                    }
#pragma unroll
                    for (int k = 0; k < 8; k++)
                        reinterpret_cast<float*>(smem + kOffW)[c * kFRows + 32 * k + lane] = ml_l(u[k]) * exp2f(ml_m(u[k]) - ml_m(ml)) * inv;
                }
                __syncwarp();
            }
            if (r == kRounds - 3 && lane == 0) asm volatile("prefetch.tensormap [%0];" ::"l"(&tmv) : "memory");
            if (r == kEarly) {
                asm volatile("cp.async.wait_all;" ::: "memory");
                __syncwarp();
            }
            if (r + kEarly < kRounds) {
                uint32_t* qrow = reinterpret_cast<uint32_t*>(smem + kOffQ + (r + kEarly) * (kD * 2));
                rotate_q(qrow, lane, cs[0][0], cs[0][1], cs[0][2], cs[0][3]);
                if (lane < 16) rotate_q(qrow, lane + 32, cs[1][0], cs[1][1], cs[1][2], cs[1][3]);
            }
            if (r >= kPR) {
                const unsigned int* mdone = &g_mdone[(team * kMG + r % kMG) * 32];
                const unsigned int need = epoch * kRounds + r - kPR + 1;
                for (int it = 0; (int)(ld_relaxed(mdone) - need) < 0; it++)
                    if (it > kSpin) __trap();
            }
            mbar_wait(sfull + 8 * (r & 1), (r >> 1) & 1);
            const float M = sc[0];
            float L = lane < kCW ? sc[lane * kScStride + 1] : 0.f;
            float acc[2][6];
#pragma unroll
            for (int ww = 0; ww < kCW; ww++) {
#pragma unroll
                for (int j = 0; j < 3; j++) {
                    const float2 t = *reinterpret_cast<const float2*>(sc + ww * kScStride + 4 + 64 * j + 2 * lane);
                    acc[ww & 1][2 * j] = ww < 2 ? t.x : acc[ww & 1][2 * j] + t.x;
                    acc[ww & 1][2 * j + 1] = ww < 2 ? t.y : acc[ww & 1][2 * j + 1] + t.y;
                }
                if ((ww & 3) == 3 && ww < 15) L += __shfl_xor_sync(0xffffffffu, L, 8 >> (ww >> 2));
            }
            L += __shfl_xor_sync(0xffffffffu, L, 1);
#pragma unroll
            for (int j = 0; j < 3; j++)
                st_rec(rec + 32 * j + lane, acc[0][2 * j] + acc[1][2 * j], acc[0][2 * j + 1] + acc[1][2 * j + 1], tag);
            if (lane == 0) st_ml(rec + 96, M, L, tag);
            __syncwarp();
            if (lane == 0) mbar_arrive(sempty + 8 * (r & 1));
        }
    } else {
        int dp[3];
#pragma unroll
        for (int j = 0; j < 3; j++) dp[j] = (64 * j + 2 * lane + 96) % kD;
        {
            const uint32_t sm0 = s2u(smem);
            if (warp < kEarly) {
                cp16(sm0 + kOffScal + threadIdx.x * 16, scal.p[lane >> 3] + (size_t)(kTeams * warp + team) * kS + row0 + (lane & 4) * (kS / 8) + (lane & 3) * 8);
            } else if (warp < 2 * kEarly && lane < 24) {
                cp16(sm0 + kOffQ + (warp - kEarly) * (kD * 2) + lane * 16, q + (size_t)(kTeams * (warp - kEarly) + team) * kD + lane * 8);
            }
            asm volatile("cp.async.commit_group;" ::: "memory");
        }
        const int p = threadIdx.x % 48, g = threadIdx.x / 48;
        const uint32_t c_lo = ld_pair(qcos + 2 * p), c_hi = ld_pair(qcos + 2 * p + 96);
        const uint32_t s_lo = ld_pair(qsin + 2 * p), s_hi = ld_pair(qsin + 2 * p + 96);
        float kc[kR][6], ks[kR][6];
        asm volatile("bar.sync 2, %0;" ::"n"(kThreads) : "memory");
        const int half = warp / (kCW / 2);
        const uint32_t fullh = full0 + 8 * half, emptyh = empty0 + 8 * half;
        mbar_wait(fullh, 0);
#pragma unroll
        for (int i = 0; i < kR; i++) {
            const unsigned char* cb = smem + half * (kHalf / 2) + (warp * kR + i) * (kD * 2);
#pragma unroll
            for (int j = 0; j < 3; j++) {
                const uint32_t uc = *reinterpret_cast<const uint32_t*>(cb + 128 * j + 4 * lane);
                const uint32_t us = *reinterpret_cast<const uint32_t*>(cb + kHalf / 2 + 2 * dp[j]);
                kc[i][2 * j] = bf_lo(uc); kc[i][2 * j + 1] = bf_hi(uc);
                const float sg = (j == 0 || (j == 1 && lane < 16)) ? 1.f : -1.f;
                ks[i][2 * j] = sg * bf_lo(us); ks[i][2 * j + 1] = sg * bf_hi(us);
            }
        }
        __syncwarp();
        if (lane == 0) mbar_arrive(emptyh);
        asm volatile("cp.async.wait_group 0;" ::: "memory");
        asm volatile("bar.sync 1, %0;" ::"n"(kCW * 32) : "memory");
        if (g < kEarly) rotate_q(reinterpret_cast<uint32_t*>(smem + kOffQ + g * (kD * 2)), p, c_lo, c_hi, s_lo, s_hi);
        asm volatile("bar.sync 1, %0;" ::"n"(kCW * 32) : "memory");
        const float scale_log2e = 1.4426950408889634f * rsqrtf((float)kD);
        float* my0 = reinterpret_cast<float*>(smem + kOffSc) + warp * kScStride;

        float* s_max = reinterpret_cast<float*>(smem + kOffMax);
        int slot = 1;
        uint32_t ph = 0;
        float lgc[kR] = {0.f, 0.f, 0.f, 0.f};
        for (int it = 0; it <= kRounds; it++) {
            float lg[kR];
            if (it < kRounds) {
                float qa[6], qb[6];
#pragma unroll
                for (int j = 0; j < 3; j++) {
                    const uint32_t qo = *reinterpret_cast<const uint32_t*>(smem + kOffQ + it * (kD * 2) + 2 * (64 * j + 2 * lane));
                    const uint32_t qp = *reinterpret_cast<const uint32_t*>(smem + kOffQ + it * (kD * 2) + 2 * dp[j]);
                    qa[2 * j] = bf_lo(qo); qa[2 * j + 1] = bf_hi(qo);
                    qb[2 * j] = bf_lo(qp); qb[2 * j + 1] = bf_hi(qp);
                }
                const unsigned char* sp = smem + kOffScal + it * (4 * kRows * 2) + warp * (kR * 2);
                const uint2 uks = *reinterpret_cast<const uint2*>(sp);
                const uint2 ukz = *reinterpret_cast<const uint2*>(sp + kRows * 2);
                const float kz[4] = {bf_lo(ukz.x), bf_hi(ukz.x), bf_lo(ukz.y), bf_hi(ukz.y)};
                const float sk[4] = {bf_lo(uks.x), bf_hi(uks.x), bf_lo(uks.y), bf_hi(uks.y)};
                mbar_wait(fullh + 16 * slot, ph);
                if ((threadIdx.x & 255) < kNP) asm volatile("red.relaxed.gpu.global.add.u32 [%0], 1;" ::"l"(g_prog + lane * 1024) : "memory");
                const unsigned char* kb = smem + slot * kChunk + warp * (kR * kRowBytes) + lane * 8;
#pragma unroll
                for (int i = 0; i < kR; i++) {
                    float dot = 0.f;
#pragma unroll
                    for (int j = 0; j < 3; j++) {
                        const int2 kk = *reinterpret_cast<const int2*>(kb + i * kRowBytes + 256 * j);
                        const float e0 = qa[2 * j] * kc[i][2 * j] + qb[2 * j] * ks[i][2 * j];
                        const float e1 = qa[2 * j + 1] * kc[i][2 * j + 1] + qb[2 * j + 1] * ks[i][2 * j + 1];
                        dot = fmaf((float)kk.x - kz[i], e0, dot);
                        dot = fmaf((float)kk.y - kz[i], e1, dot);
                    }
                    lg[i] = dot;
                }
                __syncwarp();
                if (lane == 0) mbar_arrive(emptyh + 16 * slot);
                if (++slot == kNS) { slot = 0; ph ^= 1; }
#pragma unroll
                for (int o = 16; o > 0; o >>= 1) {
#pragma unroll
                    for (int i = 0; i < kR; i++) lg[i] += __shfl_xor_sync(0xffffffffu, lg[i], o);
                }
                float mw = -INFINITY;
#pragma unroll
                for (int i = 0; i < kR; i++) {
                    lg[i] = lg[i] * sk[i] * scale_log2e;
                    mw = fmaxf(mw, lg[i]);
                }
                if (lane == 0) {
                    s_max[(it & 3) * kCW + warp] = mw;
                    mbar_arrive(mxbar + 8 * (it & 1));
                }
            }
            if (it > 0) {
                const int r = it - 1;
                float* my = my0 + (r & 1) * (kCW * kScStride);
                const int df = deferred_to(4 * half + m / 8, r);
                const unsigned char* sp = smem + kOffScal + r * (4 * kRows * 2) + warp * (kR * 2);
                const uint2 uvs = *reinterpret_cast<const uint2*>(sp + 2 * kRows * 2);
                const uint2 uvz = *reinterpret_cast<const uint2*>(sp + 3 * kRows * 2);
                const float vz[4] = {bf_lo(uvz.x), bf_hi(uvz.x), bf_lo(uvz.y), bf_hi(uvz.y)};
                const float sv[4] = {bf_lo(uvs.x), bf_hi(uvs.x), bf_lo(uvs.y), bf_hi(uvs.y)};
                mbar_wait(mxbar + 8 * (r & 1), (r >> 1) & 1);
                float M;
                {
                    const float4* pm4 = reinterpret_cast<const float4*>(s_max + (r & 3) * kCW);
                    const float4 m0 = pm4[0], m1 = pm4[1], m2 = pm4[2], m3 = pm4[3];
                    M = fmaxf(fmaxf(fmaxf(fmaxf(m0.x, m0.y), fmaxf(m0.z, m0.w)), fmaxf(fmaxf(m1.x, m1.y), fmaxf(m1.z, m1.w))),
                              fmaxf(fmaxf(fmaxf(m2.x, m2.y), fmaxf(m2.z, m2.w)), fmaxf(fmaxf(m3.x, m3.y), fmaxf(m3.z, m3.w))));
                }
                float lw = 0.f, cz = 0.f, pv[kR];
#pragma unroll
                for (int i = 0; i < kR; i++) {
                    const float p = exp2f(lgc[i] - M);
                    lw += p;
                    pv[i] = p * sv[i];
                    cz = fmaf(pv[i], vz[i], cz);
                }
                mbar_wait(sempty + 8 * (r & 1), ((r >> 1) & 1) ^ 1);
                if (lane == 0) { my[0] = M; my[1] = lw; }
                float acc[6] = {-cz, -cz, -cz, -cz, -cz, -cz};
                if (df < kF) {
                    if (lane < kR)
                        st_ml(g_lg + ((team * kFHeads + r - kDef0) * kF + df) * kFRows + (m % 8) * kHRows + (warp % 8) * kR + lane, M,
                              lane == 0 ? pv[0] : lane == 1 ? pv[1] : lane == 2 ? pv[2] : pv[3], s_misc[0] % 255u + 1u);
                } else {
                    mbar_wait(fullh + 16 * slot, ph);
                    if ((threadIdx.x & 255) < kNP) asm volatile("red.relaxed.gpu.global.add.u32 [%0], 1;" ::"l"(g_prog + lane * 1024) : "memory");
                    const unsigned char* vb = smem + slot * kChunk + warp * (kR * kRowBytes) + lane * 8;
#pragma unroll
                    for (int i = 0; i < kR; i++) {
#pragma unroll
                        for (int j = 0; j < 3; j++) {
                            const int2 vv = *reinterpret_cast<const int2*>(vb + i * kRowBytes + 256 * j);
                            acc[2 * j] = fmaf(pv[i], (float)vv.x, acc[2 * j]);
                            acc[2 * j + 1] = fmaf(pv[i], (float)vv.y, acc[2 * j + 1]);
                        }
                    }
                    __syncwarp();
                    if (lane == 0) mbar_arrive(emptyh + 16 * slot);
                    if (++slot == kNS) { slot = 0; ph ^= 1; }
                }
#pragma unroll
                for (int j = 0; j < 3; j++)
                    *reinterpret_cast<float2*>(my + 4 + 64 * j + 2 * lane) = make_float2(acc[2 * j], acc[2 * j + 1]);
                __syncwarp();
                if (lane == 0) mbar_arrive(sfull + 8 * (r & 1));
            }
#pragma unroll
            for (int i = 0; i < kR; i++) lgc[i] = lg[i];
        }
        {
            const int cp = lane < kFW / 2 ? lane : 0;
            const int ft = threadIdx.x < kFW ? threadIdx.x : 0;
            const float fin = reinterpret_cast<const float*>(smem + kOffFin)[ft];
            __nv_bfloat16* op = out + (size_t)(kTeams * (kDef0 + m / kFG) + team) * kD + (m % kFG) * kFW + ft;
            float a0 = 0.f, a1 = 0.f, b0 = 0.f, b1 = 0.f;
#pragma unroll 1
            for (int f = 0; f < kF; f++) {
                const float* sw = reinterpret_cast<const float*>(smem + kOffW) + f * kFRows + (warp >> 2) * 16 + (warp & 3) * 4;
                const unsigned char* vb = smem + slot * kChunk + ((warp >> 2) * 16 + (warp & 3) * 4) * (kFW * 4) + cp * 8;
                const uint32_t fb = fine + (f * kFBoxes + (warp >> 2)) * 8;
                float* part = reinterpret_cast<float*>(smem + kOffPart) + f * kPartSize;
                float4 w[4];
#pragma unroll
                for (int k = 0; k < 4; k++) w[k] = *reinterpret_cast<const float4*>(sw + 64 * k);
#pragma unroll
                for (int k = 0; k < 4; k++) {
                    mbar_wait(fb + 32 * k, 0);
                    if ((k & 1) && warp == kCW - 1 && lane < kNP && f < kF - 1) asm volatile("red.relaxed.gpu.global.add.u32 [%0], 1;" ::"l"(g_prog + lane * 1024) : "memory");
                    const int2 v0 = *reinterpret_cast<const int2*>(vb + k * (64 * kFW * 4));
                    const int2 v1 = *reinterpret_cast<const int2*>(vb + k * (64 * kFW * 4) + kFW * 4);
                    const int2 v2 = *reinterpret_cast<const int2*>(vb + k * (64 * kFW * 4) + 2 * kFW * 4);
                    const int2 v3 = *reinterpret_cast<const int2*>(vb + k * (64 * kFW * 4) + 3 * kFW * 4);
                    a0 = fmaf(w[k].x, (float)v0.x, a0); a1 = fmaf(w[k].x, (float)v0.y, a1);
                    b0 = fmaf(w[k].y, (float)v1.x, b0); b1 = fmaf(w[k].y, (float)v1.y, b1);
                    a0 = fmaf(w[k].z, (float)v2.x, a0); a1 = fmaf(w[k].z, (float)v2.y, a1);
                    b0 = fmaf(w[k].w, (float)v3.x, b0); b1 = fmaf(w[k].w, (float)v3.y, b1);
                }
                if (lane < kFW / 2) {
                    part[lane * kPartStride + warp] = a0 + b0;
                    part[kPartOdd + lane * kPartStride + warp] = a1 + b1;
                }
                if (warp >= 2) {
                    asm volatile("bar.arrive %0, %1;" ::"r"(3 + f), "n"(kCW * 32) : "memory");
                } else {
                    asm volatile("bar.sync %0, %1;" ::"r"(3 + f), "n"(kCW * 32) : "memory");
                    const float4* ps = reinterpret_cast<const float4*>(part + (ft & 1) * kPartOdd + (ft >> 1) * kPartStride);
                    const float4 p0 = ps[0], p1 = ps[1], p2 = ps[2], p3 = ps[3];
                    const float sum = (((p0.x + p0.y) + (p0.z + p0.w)) + ((p1.x + p1.y) + (p1.z + p1.w))) +
                                      (((p2.x + p2.y) + (p2.z + p2.w)) + ((p3.x + p3.y) + ((p3.z + p3.w) + fin)));
                    asm volatile("{\n.reg .pred p;\n.reg .b16 h;\nsetp.ne.u32 p, %2, 0;\ncvt.rn.bf16.f32 h, %1;\n@p st.global.b16 [%0], h;\n}"
                                 ::"l"(op), "f"(sum), "r"((uint32_t)(f == kF - 1 && threadIdx.x < kFW)) : "memory");
                }
                if (++slot == kNS) slot = 0;
            }
        }
    }
}

__global__ void __launch_bounds__(256)
attn_fallback(const __nv_bfloat16* __restrict__ q, const int* __restrict__ qk,
              const __nv_bfloat16* __restrict__ ksc, const __nv_bfloat16* __restrict__ kzp,
              const int* __restrict__ qv, const __nv_bfloat16* __restrict__ vsc,
              const __nv_bfloat16* __restrict__ vzp, const __nv_bfloat16* __restrict__ qcos,
              const __nv_bfloat16* __restrict__ qsin, const __nv_bfloat16* __restrict__ kcos,
              const __nv_bfloat16* __restrict__ ksin, __nv_bfloat16* __restrict__ out) {
    __shared__ float qr[kD], lg[kS], red[8];
    const int h = blockIdx.x, t = threadIdx.x, warp = t >> 5, lane = t & 31;
    if (t < kD) {
        const float x = __bfloat162float(q[h * kD + t]);
        const float y = t < kD / 2 ? -__bfloat162float(q[h * kD + t + kD / 2]) : __bfloat162float(q[h * kD + t - kD / 2]);
        qr[t] = bf_round(bf_round(x * __bfloat162float(qcos[t])) + bf_round(y * __bfloat162float(qsin[t])));
    }
    __syncthreads();
    const float scale_log2e = 1.4426950408889634f * rsqrtf((float)kD);
    float mw = -INFINITY;
    for (int s = warp; s < kS; s += 8) {
        const size_t row = (size_t)h * kS + s;
        const float z = __bfloat162float(kzp[row]);
        float dot = 0.f;
        for (int d = lane; d < kD; d += 32) {
            const int dp = d < kD / 2 ? d + kD / 2 : d - kD / 2;
            const float sn = __bfloat162float(ksin[s * kD + dp]);
            const float e = qr[d] * __bfloat162float(kcos[s * kD + d]) + qr[dp] * (d < kD / 2 ? sn : -sn);
            dot = fmaf((float)qk[row * kD + d] - z, e, dot);
        }
        for (int o = 16; o > 0; o >>= 1) dot += __shfl_xor_sync(0xffffffffu, dot, o);
        dot = dot * __bfloat162float(ksc[row]) * scale_log2e;
        if (lane == 0) lg[s] = dot;
        mw = fmaxf(mw, dot);
    }
    if (lane == 0) red[warp] = mw;
    __syncthreads();
    float M = red[0];
    for (int i = 1; i < 8; i++) M = fmaxf(M, red[i]);
    __syncthreads();
    float l = 0.f;
    for (int s = t; s < kS; s += 256) { const float p = exp2f(lg[s] - M); l += p; lg[s] = p; }
    for (int o = 16; o > 0; o >>= 1) l += __shfl_xor_sync(0xffffffffu, l, o);
    if (lane == 0) red[warp] = l;
    __syncthreads();
    float L = 0.f;
    for (int i = 0; i < 8; i++) L += red[i];
    if (t < kD) {
        float acc = 0.f;
        for (int s = 0; s < kS; s++) {
            const size_t row = (size_t)h * kS + s;
            acc = fmaf(lg[s] * __bfloat162float(vsc[row]), (float)qv[row * kD + t] - __bfloat162float(vzp[row]), acc);
        }
        out[h * kD + t] = __float2bfloat16_rn(acc / L);
    }
}

}

extern "C" void kernel_launch(void* const* d_in, const int* in_sizes, int n_in, void* d_out, int out_size) {
    const __nv_bfloat16* q = (const __nv_bfloat16*)d_in[0];
    const int* qk = (const int*)d_in[1];
    const __nv_bfloat16* ksc = (const __nv_bfloat16*)d_in[2];
    const __nv_bfloat16* kzp = (const __nv_bfloat16*)d_in[3];
    const int* qv = (const int*)d_in[4];
    const __nv_bfloat16* vsc = (const __nv_bfloat16*)d_in[5];
    const __nv_bfloat16* vzp = (const __nv_bfloat16*)d_in[6];
    const __nv_bfloat16* qcos = (const __nv_bfloat16*)d_in[7];
    const __nv_bfloat16* qsin = (const __nv_bfloat16*)d_in[8];
    const __nv_bfloat16* kcos = (const __nv_bfloat16*)d_in[9];
    const __nv_bfloat16* ksin = (const __nv_bfloat16*)d_in[10];

    typedef CUresult (*EncodeFn)(CUtensorMap*, CUtensorMapDataType, cuuint32_t, void*, const cuuint64_t*, const cuuint64_t*,
                                 const cuuint32_t*, const cuuint32_t*, CUtensorMapInterleave, CUtensorMapSwizzle,
                                 CUtensorMapL2promotion, CUtensorMapFloatOOBfill);
    static EncodeFn encode = nullptr;
    static int by_sm = 0;
    static int mode = 0;
    if (!mode) {
        int dev = 0, sms = 0, occ = 0;
        cudaGetDevice(&dev);
        cudaDeviceGetAttribute(&sms, cudaDevAttrMultiProcessorCount, dev);
        cudaError_t e = cudaFuncSetAttribute(attn_kernel, cudaFuncAttributeMaxDynamicSharedMemorySize, kSmemBytes);
        if (e == cudaSuccess) e = cudaOccupancyMaxActiveBlocksPerMultiprocessor(&occ, attn_kernel, kThreads, kSmemBytes);
        void* fn = nullptr;
        cudaDriverEntryPointQueryResult qr;
        if (e == cudaSuccess) e = cudaGetDriverEntryPoint("cuTensorMapEncodeTiled", &fn, cudaEnableDefault, &qr);
        encode = (EncodeFn)fn;
        mode = (e == cudaSuccess && fn && occ * sms >= kGrid) ? 1 : 2;
        (void)cudaGetLastError();
        by_sm = sms == kGrid && occ == 1;
    }
    CUtensorMap tmv;
    bool fast = mode == 1;
    if (fast) {
        const cuuint64_t dims[2] = {(cuuint64_t)kD, (cuuint64_t)kNH * kS}, strides[1] = {(cuuint64_t)kRowBytes};
        const cuuint32_t box[2] = {(cuuint32_t)kFW, (cuuint32_t)(kFRows / kFBoxes)}, es[2] = {1, 1};
        fast = encode(&tmv, CU_TENSOR_MAP_DATA_TYPE_INT32, 2, (void*)qv, dims, strides, box, es, CU_TENSOR_MAP_INTERLEAVE_NONE,
                      CU_TENSOR_MAP_SWIZZLE_NONE, CU_TENSOR_MAP_L2_PROMOTION_L2_128B, CU_TENSOR_MAP_FLOAT_OOB_FILL_NONE) == CUDA_SUCCESS;
    }
    if (fast)
        attn_kernel<<<kGrid, kThreads, kSmemBytes>>>(Scalars{{ksc, kzp, vsc, vzp}}, qk, by_sm, kcos, ksin, qv, q, qcos, qsin,
                                                     (__nv_bfloat16*)d_out, tmv);
    else
        attn_fallback<<<kNH, 256>>>(q, qk, ksc, kzp, qv, vsc, vzp, qcos, qsin, kcos, ksin, (__nv_bfloat16*)d_out);
}
```

```cpp
#include <cuda_runtime.h>
#include <cuda.h>
#include <cuda_bf16.h>
#include <stdint.h>

namespace {

constexpr int kB = 8, kH = 32, kS = 2048, kD = 192;
constexpr int kNH = kB * kH;
constexpr int kTeams = 4;
constexpr int kSlots = 32;
constexpr int kRows = kS / kSlots;
constexpr int kRounds = kNH / kTeams;
constexpr int kStream = kTeams * kSlots;
constexpr int kGrid = kStream + kTeams;
constexpr int kCW = 16;
constexpr int kR = kRows / kCW;
constexpr int kNP = 2;
constexpr int kThreads = (kCW + 2 + kNP) * 32;
constexpr int kRowBytes = kD * 4;
constexpr int kChunk = kRows * kRowBytes;
constexpr int kNS = 3;
constexpr int kHalf = kChunk / 2;
constexpr int kHRows = kRows / 2;
constexpr int kLead = 236;
constexpr int kLeadEnd = 215;
constexpr int kRampEnd = 12, kRampStep = 70;
constexpr int kWaveSlot = 2, kWaveHalf = 48, kWaveV = 16, kWaveRamp = 8;
constexpr uint32_t kRate = 69, kAhead = 256;
constexpr int kSample = 4;
constexpr int kPollSleep = 300;
constexpr int kQuick = 20;
constexpr int kSleep = 200;
constexpr int kPR = 12;
constexpr int kScStride = 196;
constexpr int kOffScal = kNS * kChunk;
constexpr int kOffQ = kOffScal + kRounds * 4 * kRows * 2;
constexpr int kOffSc = kOffQ + kRounds * kD * 2;
constexpr int kOffBar = kOffSc + 2 * kCW * kScStride * 4;
constexpr int kF = 3;
constexpr int kFG = 4;
constexpr int kFW = kD / kFG;
constexpr int kFRows = kRows * kFG;
constexpr int kFHeads = kSlots / kFG;
constexpr int kDef0 = 16;
constexpr int kEarly = 4;
constexpr int kFBoxes = 16;
constexpr int kPrep = 40;
constexpr int kOffW = kOffScal;
constexpr int kOffFin = kOffW + kF * kFRows * 4;
constexpr int kPartStride = 20, kPartOdd = (kFW / 2) * kPartStride + 16, kPartSize = 2 * kPartOdd;
constexpr int kOffPart = kOffFin + kFW * 4;
constexpr int kOffMisc = kOffBar + (4 * kNS + 6 + kF * kFBoxes) * 8;
constexpr int kOffMax = kOffMisc + 32;
constexpr int kSmemBytes = kOffMax + 4 * kCW * 4;
constexpr int kRecWords = kD / 2;
constexpr int kHeadWords = kSlots * (kRecWords + 1);
constexpr int kPreWords = 112;
constexpr int kMG = 6;
static_assert(kNS >= 3, "ring");
static_assert(kOffBar % 8 == 0 && kOffSc % 16 == 0 && kOffMax % 16 == 0, "alignment");
static_assert(kPR % kMG == 0, "ring");
static_assert(kNP == 2 && kOffMisc % 16 == 0 && kLeadEnd >= kStream && kS == kFHeads * kFRows && kFHeads == 8, "schedule");
static_assert(kSmemBytes <= 232448, "smem");
static_assert(kDef0 + kFHeads < kPrep && kPrep + 16 + 3 < kRounds && kEarly + kF * kFBoxes + 3 < kRounds && kOffPart <= kOffScal + (kPrep - 2) * 4 * kRows * 2 &&
              kOffPart + kF * kPartSize * 4 <= kOffScal + (kRounds - 2) * 4 * kRows * 2 && kF <= kNS && kFBoxes == kCW, "deferred rounds");

__device__ __align__(128) unsigned long long g_rec[kPR * kTeams * kHeadWords];
__device__ __align__(128) unsigned long long g_pre[kTeams * kFHeads * kPreWords];
__device__ __align__(128) unsigned long long g_lg[kTeams * kFHeads * kF * kFRows];
__device__ unsigned int g_prog[(16384 + 8192) / 4 + 1];
__device__ __align__(128) unsigned int g_epoch;
__device__ __align__(128) unsigned int g_arrive;
__device__ __align__(128) unsigned int g_mdone[kTeams * kMG * 32];

constexpr int kSpin = 1 << 24;

__device__ __forceinline__ uint32_t clock32() {
    uint32_t t;
    asm volatile("mov.u32 %0, %%clock;" : "=r"(t)::"memory");
    return t;
}
__device__ __forceinline__ unsigned int* prog_counter(int j) {
    return reinterpret_cast<unsigned int*>(((reinterpret_cast<uintptr_t>(g_prog) + 16383) & ~(uintptr_t)16383) + 8192 * j);
}
__device__ __forceinline__ uint32_t s2u(const void* p) { return (uint32_t)__cvta_generic_to_shared(p); }
__device__ __forceinline__ void mbar_init(uint32_t a, int c) {
    asm volatile("mbarrier.init.shared::cta.b64 [%0], %1;" ::"r"(a), "r"(c));
}
__device__ __forceinline__ void mbar_wait(uint32_t a, uint32_t ph) {
    uint32_t ok;
    for (int it = 0;; it++) {
        asm volatile(
            "{\n.reg .pred p;\nmbarrier.try_wait.parity.shared::cta.b64 p, [%1], %2;\nselp.u32 %0, 1, 0, p;\n}"
            : "=r"(ok) : "r"(a), "r"(ph) : "memory");
        if (ok) break;
        if (it > kSpin) __trap();
    }
}
__device__ __forceinline__ void mbar_arrive(uint32_t a) {
    asm volatile("mbarrier.arrive.shared::cta.b64 _, [%0];" ::"r"(a) : "memory");
}
__device__ __forceinline__ void mbar_expect(uint32_t a, uint32_t bytes) {
    asm volatile("mbarrier.arrive.expect_tx.shared::cta.b64 _, [%0], %1;" ::"r"(a), "r"(bytes) : "memory");
}
__device__ __forceinline__ void bulk_g2s_stream(uint32_t dst, const void* src, uint32_t bytes, uint32_t mbar, uint64_t pol) {
    asm volatile("cp.async.bulk.shared::cluster.global.mbarrier::complete_tx::bytes.L2::cache_hint [%0], [%1], %2, [%3], %4;"
                 ::"r"(dst), "l"(src), "r"(bytes), "r"(mbar), "l"(pol) : "memory");
}
__device__ __forceinline__ void bulk_g2s(uint32_t dst, const void* src, uint32_t bytes, uint32_t mbar) {
    asm volatile("cp.async.bulk.shared::cluster.global.mbarrier::complete_tx::bytes [%0], [%1], %2, [%3];"
                 ::"r"(dst), "l"(src), "r"(bytes), "r"(mbar) : "memory");
}
__device__ __forceinline__ void cp16(uint32_t dst, const void* src) {
    asm volatile("cp.async.cg.shared.global [%0], [%1], 16;" ::"r"(dst), "l"(src) : "memory");
}
__device__ __forceinline__ float bf_lo(uint32_t u) { return __uint_as_float(u << 16); }
__device__ __forceinline__ float bf_hi(uint32_t u) { return __uint_as_float(u & 0xffff0000u); }
__device__ __forceinline__ float bf_round(float x) { return __bfloat162float(__float2bfloat16_rn(x)); }
__device__ __forceinline__ uint32_t ld_pair(const __nv_bfloat16* p) {
    return __ldg(reinterpret_cast<const uint32_t*>(p));
}
__device__ __forceinline__ unsigned int ld_relaxed(const unsigned int* p) {
    unsigned int v;
    asm volatile("ld.relaxed.gpu.global.u32 %0, [%1];" : "=r"(v) : "l"(p) : "memory");
    return v;
}
__device__ __forceinline__ unsigned long long pack_rec(float a, float b, uint32_t tag) {
    const uint32_t x = (__float_as_uint(a) & ~15u) | (tag & 15u), y = (__float_as_uint(b) & ~15u) | (tag >> 4);
    return ((unsigned long long)y << 32) | x;
}
__device__ __forceinline__ void st_rec(unsigned long long* p, float a, float b, uint32_t tag) {
    asm volatile("st.relaxed.gpu.global.b64 [%0], %1;" ::"l"(p), "l"(pack_rec(a, b, tag)) : "memory");
}
__device__ __forceinline__ float rec_lo(unsigned long long w) { return __uint_as_float((uint32_t)w & ~15u); }
__device__ __forceinline__ float rec_hi(unsigned long long w) { return __uint_as_float((uint32_t)(w >> 32) & ~15u); }
__device__ __forceinline__ unsigned long long ld_rec1(const unsigned long long* p) {
    unsigned long long x;
    asm volatile("ld.relaxed.gpu.global.b64 %0, [%1];" : "=l"(x) : "l"(p) : "memory");
    return x;
}
__device__ __forceinline__ void ld_rec2(const unsigned long long* p, unsigned long long& x, unsigned long long& y) {
    asm volatile("ld.relaxed.gpu.global.v2.b64 {%0, %1}, [%2];" : "=l"(x), "=l"(y) : "l"(p) : "memory");
}
__device__ __forceinline__ uint32_t rec_bad(unsigned long long w, uint32_t tlo, uint32_t thi) {
    return (((uint32_t)w ^ tlo) | ((uint32_t)(w >> 32) ^ thi)) & 15u;
}
__device__ __forceinline__ void st_ml(unsigned long long* p, float m, float l, uint32_t tag) {
    const uint32_t y = ((__float_as_uint(l) + 0x80u) & ~0xffu) | tag;
    asm volatile("st.relaxed.gpu.global.b64 [%0], %1;" ::"l"(p), "l"(((unsigned long long)y << 32) | __float_as_uint(m)) : "memory");
}
__device__ __forceinline__ uint32_t ml_bad(unsigned long long w, uint32_t tag) { return ((uint32_t)(w >> 32) ^ tag) & 0xffu; }
__device__ __forceinline__ float ml_m(unsigned long long w) { return __uint_as_float((uint32_t)w); }
__device__ __forceinline__ float ml_l(unsigned long long w) { return __uint_as_float((uint32_t)(w >> 32) & ~0xffu); }
__device__ __forceinline__ float warp_max(float v) {
    const int b = __float_as_int(v);
    const int k = __reduce_max_sync(0xffffffffu, b ^ ((b >> 31) & 0x7fffffff));
    return __int_as_float(k ^ ((k >> 31) & 0x7fffffff));
}
__device__ __forceinline__ uint32_t round_tag(unsigned int epoch, int r) {
    constexpr unsigned kUses = (kRounds + kPR - 1) / kPR;
    return (epoch * kUses + (unsigned)(r / kPR)) % 255u + 1u;
}

__device__ __forceinline__ void rotate_q(uint32_t* qrow, int p, uint32_t c_lo, uint32_t c_hi, uint32_t s_lo, uint32_t s_hi) {
    const uint32_t lo = qrow[p], hi = qrow[p + 48];
    const float a0 = bf_round(bf_lo(lo) * bf_lo(c_lo)) + bf_round(-bf_lo(hi) * bf_lo(s_lo));
    const float a1 = bf_round(bf_hi(lo) * bf_hi(c_lo)) + bf_round(-bf_hi(hi) * bf_hi(s_lo));
    const float b0 = bf_round(bf_lo(hi) * bf_lo(c_hi)) + bf_round(bf_lo(lo) * bf_lo(s_hi));
    const float b1 = bf_round(bf_hi(hi) * bf_hi(c_hi)) + bf_round(bf_hi(lo) * bf_hi(s_hi));
    const __nv_bfloat162 ua = __floats2bfloat162_rn(a0, a1), ub = __floats2bfloat162_rn(b0, b1);
    qrow[p] = *reinterpret_cast<const uint32_t*>(&ua);
    qrow[p + 48] = *reinterpret_cast<const uint32_t*>(&ub);
}
__device__ __forceinline__ int deferred_to(int blk, int r) {
    return (unsigned)(r - kDef0) < (unsigned)kFHeads ? (blk - kF * (r - kDef0)) & (kFHeads - 1) : kF;
}

__device__ __forceinline__ unsigned role_of_sm(unsigned smid) {
    const unsigned u = smid >> 1;
    const unsigned g = u < 32 ? u & 7 : u < 60 ? 1 + (u - 32) % 7 : u < 62 ? u - 54 : 0;
    const unsigned t = u < 32 ? u >> 3 : u < 60 ? 4 + (u - 32) / 7 : u < 62 ? 8 : u - 58;
    const unsigned lin = 16 * g + (g == 7 ? 2 : 0) + 2 * t + (smid & 1);
    if (lin < 2 || lin == 48 || lin == 49) return kStream + (lin & 1) + (lin < 2 ? 0 : 2);
    const unsigned x = lin - (lin < 48 ? 2 : 4);
    return (x & 14) * 8 + (x >> 4) * 2 + (x & 1);
}
static_assert(kGrid == 132 && kTeams == 4, "role_of_sm");
struct Scalars { const __nv_bfloat16* p[4]; };

__global__ void __launch_bounds__(kThreads, 1)
attn_kernel(const __grid_constant__ Scalars scal, const int* __restrict__ qk, int by_sm, const __nv_bfloat16* __restrict__ kcos,
            const __nv_bfloat16* __restrict__ ksin, const int* __restrict__ qv, const __nv_bfloat16* __restrict__ q,
            const __nv_bfloat16* __restrict__ qcos, const __nv_bfloat16* __restrict__ qsin,
            __nv_bfloat16* __restrict__ out, const __grid_constant__ CUtensorMap tmv) {
    extern __shared__ __align__(128) unsigned char smem[];
    const int warp = threadIdx.x >> 5, lane = threadIdx.x & 31;
    const uint32_t full0 = s2u(smem + kOffBar), empty0 = full0 + 2 * kNS * 8;
    const uint32_t sfull = empty0 + 2 * kNS * 8, sempty = sfull + 16, mxbar = sempty + 16, fine = mxbar + 16;
    volatile unsigned int* s_misc = reinterpret_cast<volatile unsigned int*>(smem + kOffMisc);
    uint64_t pol = 0;

    asm volatile("prefetch.global.L2 [%0];"
                 ::"l"(reinterpret_cast<const char*>(qk) + (blockIdx.x * (kThreads / 4) + threadIdx.x / 4) * 128) : "memory");
    unsigned bid = blockIdx.x;
    if (by_sm) {
        unsigned smid, nsm;
        asm volatile("mov.u32 %0, %%smid;" : "=r"(smid));
        asm volatile("mov.u32 %0, %%nsmid;" : "=r"(nsm));
        if (nsm == kGrid) bid = role_of_sm(smid);
    }
    if (threadIdx.x == kCW * 32 && bid < kStream) {
        const int m = bid % kSlots;
        const uint32_t sm0 = s2u(smem);
        asm volatile("cp.async.bulk.prefetch.L2.global [%0], %1;"
                     ::"l"(scal.p[bid & 3] + (bid >> 2) * (kNH * kS * 4 / kStream)), "n"(kNH * kS * 4 / kStream * 2) : "memory");
        for (int i = 0; i < 2 * kNS; i++) mbar_init(full0 + 8 * i, 1);
        asm volatile("fence.mbarrier_init.release.cluster;" ::: "memory");
        asm volatile("createpolicy.fractional.L2::evict_first.b64 %0, 1.0;" : "=l"(pol));
        const int* k0 = qk + (size_t)(bid / kSlots * kS + m * kHRows) * kD;
#pragma unroll
        for (int h = 0; h < 2; h++) {
            mbar_expect(full0 + 16 + 8 * h, kHalf);
            bulk_g2s_stream(sm0 + kChunk + h * kHalf, k0 + h * (kS / 2 * kD), kHalf, full0 + 16 + 8 * h, pol);
        }
#pragma unroll
        for (int h = 0; h < 2; h++) {
            mbar_expect(full0 + 8 * h, kHalf);
            bulk_g2s(sm0 + h * kHalf, kcos + (h * (kS / 2) + m * kHRows) * kD, kHalf / 2, full0 + 8 * h);
            bulk_g2s(sm0 + h * kHalf + kHalf / 2, ksin + (h * (kS / 2) + m * kHRows) * kD, kHalf / 2, full0 + 8 * h);
        }
#pragma unroll
        for (int h = 0; h < 2; h++) {
            mbar_expect(full0 + 32 + 8 * h, kHalf);
            bulk_g2s_stream(sm0 + 2 * kChunk + h * kHalf, k0 + (kTeams * kS + h * (kS / 2)) * kD, kHalf, full0 + 32 + 8 * h, pol);
        }
    }

    if (bid >= kStream) {
        const int team = bid - kStream;
        if (threadIdx.x == 0) s_misc[0] = ld_relaxed(&g_epoch);
        __syncthreads();
        if (threadIdx.x == 0 && atomicAdd(&g_arrive, 1u) == kGrid - 1) { g_arrive = 0u; g_epoch = s_misc[0] + 1u; }
        if (warp >= 3 * kMG) return;
        const int grp = warp / 3, t = threadIdx.x - grp * 96;
        constexpr int kRecBytes = kHeadWords * 8;
        if (t == 0) {
            mbar_init(s2u(smem + kOffBar) + grp * 8, 1);
            asm volatile("fence.mbarrier_init.release.cluster;" ::: "memory");
        }
        asm volatile("bar.sync %0, 96;" ::"r"(3 + grp) : "memory");
        for (int r = grp; r < kRounds; r += kMG) {
            const int g = r % kMG;
            const int tt = threadIdx.x - g * 96, qd = tt % 48, half = tt / 48;
            const uint32_t tag = round_tag(s_misc[0], r);
            const uint32_t tlo = tag & 15u, thi = tag >> 4;
            const unsigned long long* rec = g_rec + (size_t)(r % kPR * kTeams + team) * kHeadWords;
            unsigned long long ml, x[16], y[16];
            {
                const unsigned long long* buf = reinterpret_cast<const unsigned long long*>(smem + g * kRecBytes);
                const uint32_t mb = s2u(smem + kOffBar) + g * 8;
                if (tt < 32) {
                    const int want = r == kRounds - 1 ? kQuick : kSlots;
                    for (int i2 = 0;; i2++) {
                        ml = ld_rec1(rec + kSlots * kRecWords + lane);
                        if (__popc(__ballot_sync(0xffffffffu, ml_bad(ml, tag) == 0)) >= want) break;
                        if (i2 > kSpin) __trap();
                        __nanosleep(r >= kRounds - 2 ? kSleep : 5 * kSleep);
                    }
                    if (tt == 0) {
                        mbar_expect(mb, kRecBytes);
                        bulk_g2s(s2u(buf), rec, kRecBytes, mb);
                    }
                }
                mbar_wait(mb, (r / kMG) & 1);
                ml = buf[kSlots * kRecWords + lane];
#pragma unroll
                for (int i = 0; i < 16; i++) {
                    const ulonglong2 u = *reinterpret_cast<const ulonglong2*>(buf + (half * 16 + i) * kRecWords + 2 * qd);
                    x[i] = u.x; y[i] = u.y;
                }
                const unsigned long long* po = rec + half * 16 * kRecWords + 2 * qd;
                for (int it = 0;; it++) {
                    uint32_t any = ml_bad(ml, tag);
                    if (any) ml = ld_rec1(rec + kSlots * kRecWords + lane);
#pragma unroll
                    for (int i = 0; i < 16; i++) {
                        const uint32_t bad = rec_bad(x[i], tlo, thi) | rec_bad(y[i], tlo, thi);
                        if (bad) ld_rec2(po + i * kRecWords, x[i], y[i]);
                        any |= bad;
                    }
                    if (__all_sync(0xffffffffu, any == 0)) break;
                    if (it > kSpin) __trap();
                }
            }
            const float M = ml_m(ml);
            const float MM = warp_max(M);
            const float w = exp2f(M - MM);
            float LL = w * ml_l(ml);
#pragma unroll
            for (int o = 16; o > 0; o >>= 1) LL += __shfl_xor_sync(0xffffffffu, LL, o);
            float4 a = make_float4(0.f, 0.f, 0.f, 0.f);
#pragma unroll
            for (int i = 0; i < 16; i++) {
                const float wi = __shfl_sync(0xffffffffu, w, half * 16 + i);
                a.x = fmaf(wi, rec_lo(x[i]), a.x);
                a.y = fmaf(wi, rec_hi(x[i]), a.y);
                a.z = fmaf(wi, rec_lo(y[i]), a.z);
                a.w = fmaf(wi, rec_hi(y[i]), a.w);
            }
            float* rb = reinterpret_cast<float*>(smem + kMG * kRecBytes) + (2 * g + ((r / kMG) & 1)) * kD + 4 * qd;
            if (half == 1) *reinterpret_cast<float4*>(rb) = a;
            asm volatile("bar.sync %0, 96;" ::"r"(3 + g) : "memory");
            if (half == 0) {
                const float4 u = *reinterpret_cast<float4*>(rb);
                if ((unsigned)(r - kDef0) < (unsigned)kFHeads) {
                    unsigned long long* pre = g_pre + (size_t)(team * kFHeads + r - kDef0) * kPreWords;
                    const uint32_t ptag = s_misc[0] % 255u + 1u;
                    st_rec(pre + 2 * qd, a.x + u.x, a.y + u.y, ptag);
                    st_rec(pre + 2 * qd + 1, a.z + u.z, a.w + u.w, ptag);
                    if (qd == 0) st_ml(pre + 96, MM, LL, ptag);
                } else {
                    const float inv = __fdividef(1.0f, LL);
                    const __nv_bfloat162 o0 = __floats2bfloat162_rn((a.x + u.x) * inv, (a.y + u.y) * inv);
                    const __nv_bfloat162 o1 = __floats2bfloat162_rn((a.z + u.z) * inv, (a.w + u.w) * inv);
                    uint2 ov;
                    ov.x = *reinterpret_cast<const uint32_t*>(&o0);
                    ov.y = *reinterpret_cast<const uint32_t*>(&o1);
                    *reinterpret_cast<uint2*>(out + (size_t)(kTeams * r + team) * kD + 4 * qd) = ov;
                }
            }
            if (tt == 95)
                asm volatile("st.relaxed.gpu.global.u32 [%0], %1;" ::"l"(&g_mdone[(team * kMG + g) * 32]), "r"(s_misc[0] * kRounds + r + 1) : "memory");
        }
        return;
    }

    const int m = bid % kSlots, team = bid / kSlots;
    const int row0 = m * kHRows;

    if (warp == kCW) {
        unsigned int epoch = 0;
        const size_t off0 = ((size_t)team * kS + row0) * kD;
        const uint32_t sm0 = s2u(smem);
        if (lane == 0) {
            epoch = ld_relaxed(&g_epoch);
            s_misc[0] = epoch;
            s_misc[1] = 0;
            for (int j = 0; j < kNP; j++) {
                s_misc[4 + 2 * j] = epoch * (kStream * (4 * kRounds - 2));
                s_misc[5 + 2 * j] = clock32();
            }
        }
        __syncwarp();
        asm volatile("bar.sync 2, %0;" ::"n"(kThreads) : "memory");
        if (lane == 0) {
            const unsigned int base = epoch * (kStream * (4 * kRounds - 2));
            const int phase = (2 * team - (kTeams - 1)) * (kStream / 2) + (m - kSlots / 2) * kWaveSlot;
            int use0 = kNS, use1 = kNS;
            const int* kp = qk + off0;
            const int* vp = qv + off0;
            for (int ph2 = 4; ph2 < 2 * (2 * kRounds + kF); ph2++) {
                const int p = ph2 >> 1, h = ph2 & 1;
                const bool isv = (p & 1) == 0 || p == 2 * kRounds - 1;
                const int r = p == 2 * kRounds - 1 ? kRounds - 1 : isv ? (p >> 1) - 1 : (p + 1) >> 1;
                const int ramp = max(min(min(ph2 - 4, 4 * kRounds - ph2), kWaveRamp), 0);
                const int tau = kStream * ph2 + (phase + (h ? -kWaveHalf : kWaveHalf) + (isv ? kWaveV : -kWaveV)) * ramp / kWaveRamp;
                const int gone = min(max(tau - kStream * (4 * kDef0 + 3), 0), 4 * kStream * kFHeads) * kF / (2 * kFHeads);
                const unsigned int need = base + tau - gone - max(kRampEnd - ph2, 0) * kRampStep - (p >= 2 * kRounds ? kLeadEnd : kLead);
                const bool skip = isv && deferred_to(4 * h + m / 8, r) < kF;
                const int u = h ? use1 : use0;
                const int slot = u >= kNS ? u - kNS : u;
                const uint32_t dst = sm0 + slot * kChunk + h * kHalf, fullb = full0 + 16 * slot + 8 * h;
                const int* src = (isv ? vp : kp) + (size_t)(r * kTeams * kS + h * (kS / 2)) * kD;
                if (!skip) {
                    const int un = u + 1 == 2 * kNS ? 0 : u + 1;
                    if (h) use1 = un; else use0 = un;
                    mbar_wait(fullb + 2 * kNS * 8, u >= kNS ? 0 : 1);
                    if (p < 2 * kRounds) mbar_expect(fullb, kHalf);
                }
                asm volatile("" ::"l"(src), "r"(dst) : "memory");
                if (!skip)
                    for (int it = 0;; it++) {
                        uint32_t x, tx, y, ty;
                        asm volatile("ld.volatile.shared.v4.u32 {%0, %1, %2, %3}, [%4];"
                                     : "=r"(x), "=r"(tx), "=r"(y), "=r"(ty) : "r"(sm0 + kOffMisc + 16) : "memory");
                        const uint32_t now = clock32();
                        x += min(((now - tx) * kRate) >> 10, kAhead);
                        y += min(((now - ty) * kRate) >> 10, kAhead);
                        if ((int)((x - need) & (y - need)) >= 0) break;
                        if (it > 16 * kSpin) __trap();
                    }
                if (ph2 == 2 * (2 * kRounds + kF) - 1) s_misc[1] = 1;
                if (p >= 2 * kRounds || skip) {
                    const int hi = m / kFG;
                    const int row = (kTeams * (kDef0 + hi) + team) * kS + ((kF * hi + p - 2 * kRounds) & (kFHeads - 1)) * kFRows + h * (kFRows / 2);
                    const uint32_t fb = fine + 8 * (kFBoxes / 2) * (ph2 - 4 * kRounds);
#pragma unroll 1
                    for (int w = 0; w < kFBoxes / 2; w++)
                        asm volatile("{\n.reg .pred p;\nsetp.ne.u32 p, %6, 0;\n"
                                     "@p cp.async.bulk.tensor.2d.shared::cluster.global.tile.mbarrier::complete_tx::bytes.L2::cache_hint [%0], [%1, {%2, %3}], [%4], %5;\n}"
                                     ::"r"(dst + w * (kChunk / kFBoxes)), "l"(&tmv), "r"((m % kFG) * kFW), "r"(row + w * (kFRows / kFBoxes)),
                                       "r"(fb + 8 * w), "l"(pol), "r"((uint32_t)!skip) : "memory");
                } else {
                    bulk_g2s_stream(dst, src, kHalf, fullb, pol);
                }
            }
        }
    } else if (warp >= kCW + 2) {
        asm volatile("bar.sync 2, %0;" ::"n"(kThreads) : "memory");
        if (lane == 0) {
            const int j = warp - (kCW + 2);
            for (int it = 0; !s_misc[1]; it++) {
                const uint32_t t = clock32();
                const uint32_t v = ld_relaxed(prog_counter(j));
                asm volatile("st.volatile.shared.v2.u32 [%0], {%1, %2};" ::"r"(s2u(smem) + kOffMisc + 16 + 8 * j), "r"(v), "r"(t) : "memory");
                if (s_misc[1]) break;
                if (it > kSpin) __trap();
                __nanosleep(kPollSleep);
            }
        }
    } else if (warp == kCW + 1) {
        {
            if (lane < 2 * kNS + 6) mbar_init(empty0 + 8 * lane, lane < 2 * kNS ? kCW / 2 : (lane >= 2 * kNS + 2 && lane < 2 * kNS + 4) ? 1 : kCW);
            asm volatile("fence.mbarrier_init.release.cluster;" ::: "memory");
        }
        asm volatile("bar.sync 2, %0;" ::"n"(kThreads) : "memory");
        const unsigned int epoch = s_misc[0];
        if (lane == 0 && atomicAdd(&g_arrive, 1u) == kGrid - 1) { g_arrive = 0u; g_epoch = epoch + 1u; }
        {
            const uint32_t sm0 = s2u(smem);
            const __nv_bfloat16* src = scal.p[lane >> 3] + (size_t)team * kS + row0 + (lane & 4) * (kS / 8) + (lane & 3) * 8;
            const __nv_bfloat16* qs = q + team * kD + lane * 8;
#pragma unroll 1
            for (int r = kEarly; r < kRounds; r++) {
                cp16(sm0 + kOffScal + r * 512 + lane * 16, src + (size_t)r * (kTeams * kS));
                if (lane < 24) cp16(sm0 + kOffQ + r * (kD * 2) + lane * 16, qs + r * (kTeams * kD));
                if (r == 2 * kEarly - 1 || r == kRounds - 1) asm volatile("cp.async.commit_group;" ::: "memory");
            }
        }
        uint32_t cs[2][4];
#pragma unroll
        for (int i = 0; i < 2; i++) {
            const int p = (lane + 32 * i) % 48;
            cs[i][0] = ld_pair(qcos + 2 * p); cs[i][1] = ld_pair(qcos + 2 * p + 96);
            cs[i][2] = ld_pair(qsin + 2 * p); cs[i][3] = ld_pair(qsin + 2 * p + 96);
        }
        asm volatile("cp.async.wait_group 1;" ::: "memory");
        __syncwarp();
        for (int r = 0; r < kRounds; r++) {
            const float* sc = reinterpret_cast<const float*>(smem + kOffSc) + (r & 1) * (kCW * kScStride);
            const uint32_t tag = round_tag(epoch, r);
            unsigned long long* rec = g_rec + (size_t)(r % kPR * kTeams + team) * kHeadWords;
            if (r >= kEarly && r < kEarly + kF * kFBoxes && lane == 0) {
                mbar_init(fine + 8 * (r - kEarly), 1);
                asm volatile("fence.mbarrier_init.release.cluster;" ::: "memory");
                mbar_expect(fine + 8 * (r - kEarly), kChunk / kFBoxes);
                asm volatile("fence.proxy.async.shared::cta;" ::: "memory");
            }
            if (r == kPrep + m / 2) {
                const unsigned long long* pre = g_pre + (size_t)(team * kFHeads + m / kFG) * kPreWords;
                const unsigned long long* lgp = g_lg + (size_t)(team * kFHeads + m / kFG) * (kF * kFRows);
                const uint32_t ptag = epoch % 255u + 1u;
                unsigned long long ml, po;
                for (int it = 0;; it++) {
                    ml = ld_rec1(pre + 96);
                    po = ld_rec1(pre + (m % kFG) * (kFW / 2) + lane % (kFW / 2));
                    if (!(ml_bad(ml, ptag) | rec_bad(po, ptag & 15u, ptag >> 4))) break;
                    if (it > kSpin) __trap();
                }
                const float inv = 1.0f / ml_l(ml);
                if (lane < kFW / 2) {
                    reinterpret_cast<float2*>(smem + kOffFin)[lane] = make_float2(rec_lo(po) * inv, rec_hi(po) * inv);
                }
#pragma unroll 1
                for (int c = 0; c < kF; c++) {
                    unsigned long long u[8];
                    for (int it = 0;; it++) {
                        uint32_t bad = 0;
#pragma unroll
                        for (int k = 0; k < 8; k++) {
                            u[k] = ld_rec1(lgp + c * kFRows + 32 * k + lane);
                            bad |= ml_bad(u[k], ptag);
                        }
                        if (!bad) break;
                        if (it > kSpin) __trap();
                    }
#pragma unroll
                    for (int k = 0; k < 8; k++)
                        reinterpret_cast<float*>(smem + kOffW)[c * kFRows + 32 * k + lane] = ml_l(u[k]) * exp2f(ml_m(u[k]) - ml_m(ml)) * inv;
                }
                __syncwarp();
            }
            if (r == kRounds - 3 && lane == 0) asm volatile("prefetch.tensormap [%0];" ::"l"(&tmv) : "memory");
            if (r == kEarly) {
                asm volatile("cp.async.wait_all;" ::: "memory");
                __syncwarp();
            }
            if (r + kEarly < kRounds) {
                uint32_t* qrow = reinterpret_cast<uint32_t*>(smem + kOffQ + (r + kEarly) * (kD * 2));
                rotate_q(qrow, lane, cs[0][0], cs[0][1], cs[0][2], cs[0][3]);
                if (lane < 16) rotate_q(qrow, lane + 32, cs[1][0], cs[1][1], cs[1][2], cs[1][3]);
            }
            if (r >= kPR) {
                const unsigned int* mdone = &g_mdone[(team * kMG + r % kMG) * 32];
                const unsigned int need = epoch * kRounds + r - kPR + 1;
                for (int it = 0; (int)(ld_relaxed(mdone) - need) < 0; it++)
                    if (it > kSpin) __trap();
            }
            mbar_wait(sfull + 8 * (r & 1), (r >> 1) & 1);
            const float M = sc[0];
            float L = lane < kCW ? sc[lane * kScStride + 1] : 0.f;
            float acc[2][6];
#pragma unroll
            for (int ww = 0; ww < kCW; ww++) {
#pragma unroll
                for (int j = 0; j < 3; j++) {
                    const float2 t = *reinterpret_cast<const float2*>(sc + ww * kScStride + 4 + 64 * j + 2 * lane);
                    acc[ww & 1][2 * j] = ww < 2 ? t.x : acc[ww & 1][2 * j] + t.x;
                    acc[ww & 1][2 * j + 1] = ww < 2 ? t.y : acc[ww & 1][2 * j + 1] + t.y;
                }
                if ((ww & 3) == 3 && ww < 15) L += __shfl_xor_sync(0xffffffffu, L, 8 >> (ww >> 2));
            }
            L += __shfl_xor_sync(0xffffffffu, L, 1);
#pragma unroll
            for (int j = 0; j < 3; j++)
                st_rec(rec + m * kRecWords + 32 * j + lane, acc[0][2 * j] + acc[1][2 * j], acc[0][2 * j + 1] + acc[1][2 * j + 1], tag);
            if (lane == 0) st_ml(rec + kSlots * kRecWords + m, M, L, tag);
            __syncwarp();
            if (lane == 0) mbar_arrive(sempty + 8 * (r & 1));
        }
    } else {
        int dp[3];
#pragma unroll
        for (int j = 0; j < 3; j++) dp[j] = (64 * j + 2 * lane + 96) % kD;
        {
            const uint32_t sm0 = s2u(smem);
            if (warp < kEarly) {
                cp16(sm0 + kOffScal + threadIdx.x * 16, scal.p[lane >> 3] + (size_t)(kTeams * warp + team) * kS + row0 + (lane & 4) * (kS / 8) + (lane & 3) * 8);
            } else if (warp < 2 * kEarly && lane < 24) {
                cp16(sm0 + kOffQ + (warp - kEarly) * (kD * 2) + lane * 16, q + (size_t)(kTeams * (warp - kEarly) + team) * kD + lane * 8);
            }
            asm volatile("cp.async.commit_group;" ::: "memory");
        }
        const int p = threadIdx.x % 48, g = threadIdx.x / 48;
        const uint32_t c_lo = ld_pair(qcos + 2 * p), c_hi = ld_pair(qcos + 2 * p + 96);
        const uint32_t s_lo = ld_pair(qsin + 2 * p), s_hi = ld_pair(qsin + 2 * p + 96);
        float kc[kR][6], ks[kR][6];
        asm volatile("bar.sync 2, %0;" ::"n"(kThreads) : "memory");
        unsigned int* prog = prog_counter(((m >> 1) ^ (m >> 4) ^ team) & 1);
        const int mute = (m & 1) * 256;
        const int half = warp / (kCW / 2);
        const uint32_t fullh = full0 + 8 * half, emptyh = empty0 + 8 * half;
        mbar_wait(fullh, 0);
#pragma unroll
        for (int i = 0; i < kR; i++) {
            const unsigned char* cb = smem + half * (kHalf / 2) + (warp * kR + i) * (kD * 2);
#pragma unroll
            for (int j = 0; j < 3; j++) {
                const uint32_t uc = *reinterpret_cast<const uint32_t*>(cb + 128 * j + 4 * lane);
                const uint32_t us = *reinterpret_cast<const uint32_t*>(cb + kHalf / 2 + 2 * dp[j]);
                kc[i][2 * j] = bf_lo(uc); kc[i][2 * j + 1] = bf_hi(uc);
                const float sg = (j == 0 || (j == 1 && lane < 16)) ? 1.f : -1.f;
                ks[i][2 * j] = sg * bf_lo(us); ks[i][2 * j + 1] = sg * bf_hi(us);
            }
        }
        __syncwarp();
        if (lane == 0) mbar_arrive(emptyh);
        asm volatile("cp.async.wait_group 0;" ::: "memory");
        asm volatile("bar.sync 1, %0;" ::"n"(kCW * 32) : "memory");
        if (g < kEarly) rotate_q(reinterpret_cast<uint32_t*>(smem + kOffQ + g * (kD * 2)), p, c_lo, c_hi, s_lo, s_hi);
        asm volatile("bar.sync 1, %0;" ::"n"(kCW * 32) : "memory");
        const float scale_log2e = 1.4426950408889634f * rsqrtf((float)kD);
        float* my0 = reinterpret_cast<float*>(smem + kOffSc) + warp * kScStride;

        float* s_max = reinterpret_cast<float*>(smem + kOffMax);
        int slot = 1;
        uint32_t ph = 0;
        float lgc[kR] = {0.f, 0.f, 0.f, 0.f};
        for (int it = 0; it <= kRounds; it++) {
            float lg[kR];
            if (it < kRounds) {
                float qa[6], qb[6];
#pragma unroll
                for (int j = 0; j < 3; j++) {
                    const uint32_t qo = *reinterpret_cast<const uint32_t*>(smem + kOffQ + it * (kD * 2) + 2 * (64 * j + 2 * lane));
                    const uint32_t qp = *reinterpret_cast<const uint32_t*>(smem + kOffQ + it * (kD * 2) + 2 * dp[j]);
                    qa[2 * j] = bf_lo(qo); qa[2 * j + 1] = bf_hi(qo);
                    qb[2 * j] = bf_lo(qp); qb[2 * j + 1] = bf_hi(qp);
                }
                const unsigned char* sp = smem + kOffScal + it * (4 * kRows * 2) + warp * (kR * 2);
                const uint2 uks = *reinterpret_cast<const uint2*>(sp);
                const uint2 ukz = *reinterpret_cast<const uint2*>(sp + kRows * 2);
                const float kz[4] = {bf_lo(ukz.x), bf_hi(ukz.x), bf_lo(ukz.y), bf_hi(ukz.y)};
                const float sk[4] = {bf_lo(uks.x), bf_hi(uks.x), bf_lo(uks.y), bf_hi(uks.y)};
                mbar_wait(fullh + 16 * slot, ph);
                if ((threadIdx.x & 255) == mute) asm volatile("red.relaxed.gpu.global.add.u32 [%0], %1;" ::"l"(prog), "n"(kSample) : "memory");
                const unsigned char* kb = smem + slot * kChunk + warp * (kR * kRowBytes) + lane * 8;
#pragma unroll
                for (int i = 0; i < kR; i++) {
                    float dot = 0.f;
#pragma unroll
                    for (int j = 0; j < 3; j++) {
                        const int2 kk = *reinterpret_cast<const int2*>(kb + i * kRowBytes + 256 * j);
                        const float e0 = qa[2 * j] * kc[i][2 * j] + qb[2 * j] * ks[i][2 * j];
                        const float e1 = qa[2 * j + 1] * kc[i][2 * j + 1] + qb[2 * j + 1] * ks[i][2 * j + 1];
                        dot = fmaf((float)kk.x - kz[i], e0, dot);
                        dot = fmaf((float)kk.y - kz[i], e1, dot);
                    }
                    lg[i] = dot;
                }
                __syncwarp();
                if (lane == 0) mbar_arrive(emptyh + 16 * slot);
                if (++slot == kNS) { slot = 0; ph ^= 1; }
#pragma unroll
                for (int o = 16; o > 0; o >>= 1) {
#pragma unroll
                    for (int i = 0; i < kR; i++) lg[i] += __shfl_xor_sync(0xffffffffu, lg[i], o);
                }
                float mw = -INFINITY;
#pragma unroll
                for (int i = 0; i < kR; i++) {
                    lg[i] = lg[i] * sk[i] * scale_log2e;
                    mw = fmaxf(mw, lg[i]);
                }
                if (lane == 0) {
                    s_max[(it & 3) * kCW + warp] = mw;
                    mbar_arrive(mxbar + 8 * (it & 1));
                }
            }
            if (it > 0) {
                const int r = it - 1;
                float* my = my0 + (r & 1) * (kCW * kScStride);
                const int df = deferred_to(4 * half + m / 8, r);
                const unsigned char* sp = smem + kOffScal + r * (4 * kRows * 2) + warp * (kR * 2);
                const uint2 uvs = *reinterpret_cast<const uint2*>(sp + 2 * kRows * 2);
                const uint2 uvz = *reinterpret_cast<const uint2*>(sp + 3 * kRows * 2);
                const float vz[4] = {bf_lo(uvz.x), bf_hi(uvz.x), bf_lo(uvz.y), bf_hi(uvz.y)};
                const float sv[4] = {bf_lo(uvs.x), bf_hi(uvs.x), bf_lo(uvs.y), bf_hi(uvs.y)};
                mbar_wait(mxbar + 8 * (r & 1), (r >> 1) & 1);
                float M;
                {
                    const float4* pm4 = reinterpret_cast<const float4*>(s_max + (r & 3) * kCW);
                    const float4 m0 = pm4[0], m1 = pm4[1], m2 = pm4[2], m3 = pm4[3];
                    M = fmaxf(fmaxf(fmaxf(fmaxf(m0.x, m0.y), fmaxf(m0.z, m0.w)), fmaxf(fmaxf(m1.x, m1.y), fmaxf(m1.z, m1.w))),
                              fmaxf(fmaxf(fmaxf(m2.x, m2.y), fmaxf(m2.z, m2.w)), fmaxf(fmaxf(m3.x, m3.y), fmaxf(m3.z, m3.w))));
                }
                float lw = 0.f, cz = 0.f, pv[kR];
#pragma unroll
                for (int i = 0; i < kR; i++) {
                    const float p = exp2f(lgc[i] - M);
                    lw += p;
                    pv[i] = p * sv[i];
                    cz = fmaf(pv[i], vz[i], cz);
                }
                mbar_wait(sempty + 8 * (r & 1), ((r >> 1) & 1) ^ 1);
                if (lane == 0) { my[0] = M; my[1] = lw; }
                float acc[6] = {-cz, -cz, -cz, -cz, -cz, -cz};
                if (df < kF) {
                    if (lane < kR)
                        st_ml(g_lg + ((team * kFHeads + r - kDef0) * kF + df) * kFRows + (m % 8) * kHRows + (warp % 8) * kR + lane, M,
                              lane == 0 ? pv[0] : lane == 1 ? pv[1] : lane == 2 ? pv[2] : pv[3], s_misc[0] % 255u + 1u);
                } else {
                    mbar_wait(fullh + 16 * slot, ph);
                    if ((threadIdx.x & 255) == mute) asm volatile("red.relaxed.gpu.global.add.u32 [%0], %1;" ::"l"(prog), "n"(kSample) : "memory");
                    const unsigned char* vb = smem + slot * kChunk + warp * (kR * kRowBytes) + lane * 8;
#pragma unroll
                    for (int i = 0; i < kR; i++) {
#pragma unroll
                        for (int j = 0; j < 3; j++) {
                            const int2 vv = *reinterpret_cast<const int2*>(vb + i * kRowBytes + 256 * j);
                            acc[2 * j] = fmaf(pv[i], (float)vv.x, acc[2 * j]);
                            acc[2 * j + 1] = fmaf(pv[i], (float)vv.y, acc[2 * j + 1]);
                        }
                    }
                    __syncwarp();
                    if (lane == 0) mbar_arrive(emptyh + 16 * slot);
                    if (++slot == kNS) { slot = 0; ph ^= 1; }
                }
#pragma unroll
                for (int j = 0; j < 3; j++)
                    *reinterpret_cast<float2*>(my + 4 + 64 * j + 2 * lane) = make_float2(acc[2 * j], acc[2 * j + 1]);
                __syncwarp();
                if (lane == 0) mbar_arrive(sfull + 8 * (r & 1));
            }
#pragma unroll
            for (int i = 0; i < kR; i++) lgc[i] = lg[i];
        }
        {
            const int cp = lane < kFW / 2 ? lane : 0;
            const int ft = threadIdx.x < kFW ? threadIdx.x : 0;
            const float fin = reinterpret_cast<const float*>(smem + kOffFin)[ft];
            __nv_bfloat16* op = out + (size_t)(kTeams * (kDef0 + m / kFG) + team) * kD + (m % kFG) * kFW + ft;
            float a0 = 0.f, a1 = 0.f, b0 = 0.f, b1 = 0.f;
#pragma unroll 1
            for (int f = 0; f < kF; f++) {
                const float* sw = reinterpret_cast<const float*>(smem + kOffW) + f * kFRows + (warp >> 2) * 16 + (warp & 3) * 4;
                const unsigned char* vb = smem + slot * kChunk + ((warp >> 2) * 16 + (warp & 3) * 4) * (kFW * 4) + cp * 8;
                const uint32_t fb = fine + (f * kFBoxes + (warp >> 2)) * 8;
                float* part = reinterpret_cast<float*>(smem + kOffPart) + f * kPartSize;
                float4 w[4];
#pragma unroll
                for (int k = 0; k < 4; k++) w[k] = *reinterpret_cast<const float4*>(sw + 64 * k);
#pragma unroll
                for (int k = 0; k < 4; k++) {
                    mbar_wait(fb + 32 * k, 0);
                    if ((k & 1) && threadIdx.x == kCW * 32 - 32 + mute && f < kF - 1) asm volatile("red.relaxed.gpu.global.add.u32 [%0], %1;" ::"l"(prog), "n"(kSample) : "memory");
                    const int2 v0 = *reinterpret_cast<const int2*>(vb + k * (64 * kFW * 4));
                    const int2 v1 = *reinterpret_cast<const int2*>(vb + k * (64 * kFW * 4) + kFW * 4);
                    const int2 v2 = *reinterpret_cast<const int2*>(vb + k * (64 * kFW * 4) + 2 * kFW * 4);
                    const int2 v3 = *reinterpret_cast<const int2*>(vb + k * (64 * kFW * 4) + 3 * kFW * 4);
                    a0 = fmaf(w[k].x, (float)v0.x, a0); a1 = fmaf(w[k].x, (float)v0.y, a1);
                    b0 = fmaf(w[k].y, (float)v1.x, b0); b1 = fmaf(w[k].y, (float)v1.y, b1);
                    a0 = fmaf(w[k].z, (float)v2.x, a0); a1 = fmaf(w[k].z, (float)v2.y, a1);
                    b0 = fmaf(w[k].w, (float)v3.x, b0); b1 = fmaf(w[k].w, (float)v3.y, b1);
                }
                if (lane < kFW / 2) {
                    part[lane * kPartStride + warp] = a0 + b0;
                    part[kPartOdd + lane * kPartStride + warp] = a1 + b1;
                }
                if (warp >= 2) {
                    asm volatile("bar.arrive %0, %1;" ::"r"(3 + f), "n"(kCW * 32) : "memory");
                } else {
                    asm volatile("bar.sync %0, %1;" ::"r"(3 + f), "n"(kCW * 32) : "memory");
                    const float4* ps = reinterpret_cast<const float4*>(part + (ft & 1) * kPartOdd + (ft >> 1) * kPartStride);
                    const float4 p0 = ps[0], p1 = ps[1], p2 = ps[2], p3 = ps[3];
                    const float sum = (((p0.x + p0.y) + (p0.z + p0.w)) + ((p1.x + p1.y) + (p1.z + p1.w))) +
                                      (((p2.x + p2.y) + (p2.z + p2.w)) + ((p3.x + p3.y) + ((p3.z + p3.w) + fin)));
                    asm volatile("{\n.reg .pred p;\n.reg .b16 h;\nsetp.ne.u32 p, %2, 0;\ncvt.rn.bf16.f32 h, %1;\n@p st.global.b16 [%0], h;\n}"
                                 ::"l"(op), "f"(sum), "r"((uint32_t)(f == kF - 1 && threadIdx.x < kFW)) : "memory");
                }
                if (++slot == kNS) slot = 0;
            }
        }
    }
}

__global__ void __launch_bounds__(256)
attn_fallback(const __nv_bfloat16* __restrict__ q, const int* __restrict__ qk,
              const __nv_bfloat16* __restrict__ ksc, const __nv_bfloat16* __restrict__ kzp,
              const int* __restrict__ qv, const __nv_bfloat16* __restrict__ vsc,
              const __nv_bfloat16* __restrict__ vzp, const __nv_bfloat16* __restrict__ qcos,
              const __nv_bfloat16* __restrict__ qsin, const __nv_bfloat16* __restrict__ kcos,
              const __nv_bfloat16* __restrict__ ksin, __nv_bfloat16* __restrict__ out) {
    __shared__ float qr[kD], lg[kS], red[8];
    const int h = blockIdx.x, t = threadIdx.x, warp = t >> 5, lane = t & 31;
    if (t < kD) {
        const float x = __bfloat162float(q[h * kD + t]);
        const float y = t < kD / 2 ? -__bfloat162float(q[h * kD + t + kD / 2]) : __bfloat162float(q[h * kD + t - kD / 2]);
        qr[t] = bf_round(bf_round(x * __bfloat162float(qcos[t])) + bf_round(y * __bfloat162float(qsin[t])));
    }
    __syncthreads();
    const float scale_log2e = 1.4426950408889634f * rsqrtf((float)kD);
    float mw = -INFINITY;
    for (int s = warp; s < kS; s += 8) {
        const size_t row = (size_t)h * kS + s;
        const float z = __bfloat162float(kzp[row]);
        float dot = 0.f;
        for (int d = lane; d < kD; d += 32) {
            const int dp = d < kD / 2 ? d + kD / 2 : d - kD / 2;
            const float sn = __bfloat162float(ksin[s * kD + dp]);
            const float e = qr[d] * __bfloat162float(kcos[s * kD + d]) + qr[dp] * (d < kD / 2 ? sn : -sn);
            dot = fmaf((float)qk[row * kD + d] - z, e, dot);
        }
        for (int o = 16; o > 0; o >>= 1) dot += __shfl_xor_sync(0xffffffffu, dot, o);
        dot = dot * __bfloat162float(ksc[row]) * scale_log2e;
        if (lane == 0) lg[s] = dot;
        mw = fmaxf(mw, dot);
    }
    if (lane == 0) red[warp] = mw;
    __syncthreads();
    float M = red[0];
    for (int i = 1; i < 8; i++) M = fmaxf(M, red[i]);
    __syncthreads();
    float l = 0.f;
    for (int s = t; s < kS; s += 256) { const float p = exp2f(lg[s] - M); l += p; lg[s] = p; }
    for (int o = 16; o > 0; o >>= 1) l += __shfl_xor_sync(0xffffffffu, l, o);
    if (lane == 0) red[warp] = l;
    __syncthreads();
    float L = 0.f;
    for (int i = 0; i < 8; i++) L += red[i];
    if (t < kD) {
        float acc = 0.f;
        for (int s = 0; s < kS; s++) {
            const size_t row = (size_t)h * kS + s;
            acc = fmaf(lg[s] * __bfloat162float(vsc[row]), (float)qv[row * kD + t] - __bfloat162float(vzp[row]), acc);
        }
        out[h * kD + t] = __float2bfloat16_rn(acc / L);
    }
}

}

extern "C" void kernel_launch(void* const* d_in, const int* in_sizes, int n_in, void* d_out, int out_size) {
    const __nv_bfloat16* q = (const __nv_bfloat16*)d_in[0];
    const int* qk = (const int*)d_in[1];
    const __nv_bfloat16* ksc = (const __nv_bfloat16*)d_in[2];
    const __nv_bfloat16* kzp = (const __nv_bfloat16*)d_in[3];
    const int* qv = (const int*)d_in[4];
    const __nv_bfloat16* vsc = (const __nv_bfloat16*)d_in[5];
    const __nv_bfloat16* vzp = (const __nv_bfloat16*)d_in[6];
    const __nv_bfloat16* qcos = (const __nv_bfloat16*)d_in[7];
    const __nv_bfloat16* qsin = (const __nv_bfloat16*)d_in[8];
    const __nv_bfloat16* kcos = (const __nv_bfloat16*)d_in[9];
    const __nv_bfloat16* ksin = (const __nv_bfloat16*)d_in[10];

    typedef CUresult (*EncodeFn)(CUtensorMap*, CUtensorMapDataType, cuuint32_t, void*, const cuuint64_t*, const cuuint64_t*,
                                 const cuuint32_t*, const cuuint32_t*, CUtensorMapInterleave, CUtensorMapSwizzle,
                                 CUtensorMapL2promotion, CUtensorMapFloatOOBfill);
    static EncodeFn encode = nullptr;
    static int by_sm = 0;
    static int mode = 0;
    if (!mode) {
        int dev = 0, sms = 0, occ = 0;
        cudaGetDevice(&dev);
        cudaDeviceGetAttribute(&sms, cudaDevAttrMultiProcessorCount, dev);
        cudaError_t e = cudaFuncSetAttribute(attn_kernel, cudaFuncAttributeMaxDynamicSharedMemorySize, kSmemBytes);
        if (e == cudaSuccess) e = cudaOccupancyMaxActiveBlocksPerMultiprocessor(&occ, attn_kernel, kThreads, kSmemBytes);
        void* fn = nullptr;
        cudaDriverEntryPointQueryResult qr;
        if (e == cudaSuccess) e = cudaGetDriverEntryPoint("cuTensorMapEncodeTiled", &fn, cudaEnableDefault, &qr);
        encode = (EncodeFn)fn;
        mode = (e == cudaSuccess && fn && occ * sms >= kGrid) ? 1 : 2;
        (void)cudaGetLastError();
        by_sm = sms == kGrid && occ == 1;
    }
    CUtensorMap tmv;
    bool fast = mode == 1;
    if (fast) {
        const cuuint64_t dims[2] = {(cuuint64_t)kD, (cuuint64_t)kNH * kS}, strides[1] = {(cuuint64_t)kRowBytes};
        const cuuint32_t box[2] = {(cuuint32_t)kFW, (cuuint32_t)(kFRows / kFBoxes)}, es[2] = {1, 1};
        fast = encode(&tmv, CU_TENSOR_MAP_DATA_TYPE_INT32, 2, (void*)qv, dims, strides, box, es, CU_TENSOR_MAP_INTERLEAVE_NONE,
                      CU_TENSOR_MAP_SWIZZLE_NONE, CU_TENSOR_MAP_L2_PROMOTION_L2_128B, CU_TENSOR_MAP_FLOAT_OOB_FILL_NONE) == CUDA_SUCCESS;
    }
    if (fast)
        attn_kernel<<<kGrid, kThreads, kSmemBytes>>>(Scalars{{ksc, kzp, vsc, vzp}}, qk, by_sm, kcos, ksin, qv, q, qcos, qsin,
                                                     (__nv_bfloat16*)d_out, tmv);
    else
        attn_fallback<<<kNH, 256>>>(q, qk, ksc, kzp, qv, vsc, vzp, qcos, qsin, kcos, ksin, (__nv_bfloat16*)d_out);
}
```

```cpp
#include <cuda_runtime.h>
#include <cuda.h>
#include <cuda_bf16.h>
#include <stdint.h>

namespace {

constexpr int kB = 8, kH = 32, kS = 2048, kD = 192;
constexpr int kNH = kB * kH;
constexpr int kTeams = 4;
constexpr int kSlots = 32;
constexpr int kRows = kS / kSlots;
constexpr int kRounds = kNH / kTeams;
constexpr int kStream = kTeams * kSlots;
constexpr int kGrid = kStream + kTeams;
constexpr int kCW = 16;
constexpr int kR = kRows / kCW;
constexpr int kNP = 2;
constexpr int kThreads = (kCW + 2 + kNP) * 32;
constexpr int kRowBytes = kD * 4;
constexpr int kChunk = kRows * kRowBytes;
constexpr int kNS = 3;
constexpr int kHalf = kChunk / 2;
constexpr int kHRows = kRows / 2;
constexpr int kLead = 236;
constexpr int kLeadEnd = 215;
constexpr int kRampEnd = 12, kRampStep = 70;
constexpr int kWaveSlot = 2, kWaveHalf = 48, kWaveV = 16, kWaveRamp = 8;
constexpr uint32_t kRate = 69, kAhead = 256;
constexpr int kSample = 4;
constexpr int kPollSleep = 300;
constexpr int kQuick = 20;
constexpr int kSleep = 200;
constexpr int kPR = 12;
constexpr int kScStride = 196;
constexpr int kOffScal = kNS * kChunk;
constexpr int kOffQ = kOffScal + kRounds * 4 * kRows * 2;
constexpr int kOffSc = kOffQ + kRounds * kD * 2;
constexpr int kOffBar = kOffSc + 2 * kCW * kScStride * 4;
constexpr int kF = 3;
constexpr int kFG = 4;
constexpr int kFW = kD / kFG;
constexpr int kFRows = kRows * kFG;
constexpr int kFHeads = kSlots / kFG;
constexpr int kDef0 = 16;
constexpr int kEarly = 4;
constexpr int kFBoxes = 16;
constexpr int kPrep = 40;
constexpr int kOffW = kOffScal;
constexpr int kOffFin = kOffW + kF * kFRows * 4;
constexpr int kPartStride = 20, kPartOdd = (kFW / 2) * kPartStride + 16, kPartSize = 2 * kPartOdd;
constexpr int kOffPart = kOffFin + kFW * 4;
constexpr int kOffMisc = kOffBar + (4 * kNS + 6 + kF * kFBoxes) * 8;
constexpr int kOffMax = kOffMisc + 32;
constexpr int kSmemBytes = kOffMax + 4 * kCW * 4;
constexpr int kRecWords = kD / 2;
constexpr int kHeadWords = kSlots * (kRecWords + 1);
constexpr int kPreWords = 112;
constexpr int kMG = 6;
static_assert(kNS >= 3, "ring");
static_assert(kOffBar % 8 == 0 && kOffSc % 16 == 0 && kOffMax % 16 == 0, "alignment");
static_assert(kPR % kMG == 0, "ring");
static_assert(kNP == 2 && kOffMisc % 16 == 0 && kLeadEnd >= kStream && kS == kFHeads * kFRows && kFHeads == 8, "schedule");
static_assert(kSmemBytes <= 232448, "smem");
static_assert(kDef0 + kFHeads < kPrep && kPrep + 16 + 3 < kRounds && kEarly + kF * kFBoxes + 3 < kRounds && kOffPart <= kOffScal + (kPrep - 2) * 4 * kRows * 2 &&
              kOffPart + kF * kPartSize * 4 <= kOffScal + (kRounds - 2) * 4 * kRows * 2 && kF <= kNS && kFBoxes == kCW, "deferred rounds");

__device__ __align__(128) unsigned long long g_rec[kPR * kTeams * kHeadWords];
__device__ __align__(128) unsigned long long g_pre[kTeams * kFHeads * kPreWords];
__device__ __align__(128) unsigned long long g_lg[kTeams * kFHeads * kF * kFRows];
__device__ unsigned int g_prog[(16384 + 8192) / 4 + 1];
__device__ __align__(128) unsigned int g_epoch;
__device__ __align__(128) unsigned int g_arrive;
__device__ __align__(128) unsigned int g_mdone[kTeams * kMG * 32];

constexpr int kSpin = 1 << 24;

__device__ __forceinline__ uint32_t clock32() {
    uint32_t t;
    asm volatile("mov.u32 %0, %%clock;" : "=r"(t)::"memory");
    return t;
}
__device__ __forceinline__ unsigned int* prog_counter(int j) {
    return reinterpret_cast<unsigned int*>(((reinterpret_cast<uintptr_t>(g_prog) + 16383) & ~(uintptr_t)16383) + 8192 * j);
}
__device__ __forceinline__ uint32_t s2u(const void* p) { return (uint32_t)__cvta_generic_to_shared(p); }
__device__ __forceinline__ void mbar_init(uint32_t a, int c) {
    asm volatile("mbarrier.init.shared::cta.b64 [%0], %1;" ::"r"(a), "r"(c));
}
__device__ __forceinline__ void mbar_wait(uint32_t a, uint32_t ph) {
    uint32_t ok;
    for (int it = 0;; it++) {
        asm volatile(
            "{\n.reg .pred p;\nmbarrier.try_wait.parity.shared::cta.b64 p, [%1], %2;\nselp.u32 %0, 1, 0, p;\n}"
            : "=r"(ok) : "r"(a), "r"(ph) : "memory");
        if (ok) break;
        if (it > kSpin) __trap();
    }
}
__device__ __forceinline__ void mbar_arrive(uint32_t a) {
    asm volatile("mbarrier.arrive.shared::cta.b64 _, [%0];" ::"r"(a) : "memory");
}
__device__ __forceinline__ void mbar_expect(uint32_t a, uint32_t bytes) {
    asm volatile("mbarrier.arrive.expect_tx.shared::cta.b64 _, [%0], %1;" ::"r"(a), "r"(bytes) : "memory");
}
__device__ __forceinline__ void bulk_g2s_stream(uint32_t dst, const void* src, uint32_t bytes, uint32_t mbar, uint64_t pol) {
    asm volatile("cp.async.bulk.shared::cluster.global.mbarrier::complete_tx::bytes.L2::cache_hint [%0], [%1], %2, [%3], %4;"
                 ::"r"(dst), "l"(src), "r"(bytes), "r"(mbar), "l"(pol) : "memory");
}
__device__ __forceinline__ void bulk_g2s(uint32_t dst, const void* src, uint32_t bytes, uint32_t mbar) {
    asm volatile("cp.async.bulk.shared::cluster.global.mbarrier::complete_tx::bytes [%0], [%1], %2, [%3];"
                 ::"r"(dst), "l"(src), "r"(bytes), "r"(mbar) : "memory");
}
__device__ __forceinline__ void cp16(uint32_t dst, const void* src) {
    asm volatile("cp.async.cg.shared.global [%0], [%1], 16;" ::"r"(dst), "l"(src) : "memory");
}
__device__ __forceinline__ float bf_lo(uint32_t u) { return __uint_as_float(u << 16); }
__device__ __forceinline__ float bf_hi(uint32_t u) { return __uint_as_float(u & 0xffff0000u); }
__device__ __forceinline__ float bf_round(float x) { return __bfloat162float(__float2bfloat16_rn(x)); }
__device__ __forceinline__ uint32_t ld_pair(const __nv_bfloat16* p) {
    return __ldg(reinterpret_cast<const uint32_t*>(p));
}
__device__ __forceinline__ unsigned int ld_relaxed(const unsigned int* p) {
    unsigned int v;
    asm volatile("ld.relaxed.gpu.global.u32 %0, [%1];" : "=r"(v) : "l"(p) : "memory");
    return v;
}
__device__ __forceinline__ unsigned long long pack_rec(float a, float b, uint32_t tag) {
    const uint32_t x = (__float_as_uint(a) & ~15u) | (tag & 15u), y = (__float_as_uint(b) & ~15u) | (tag >> 4);
    return ((unsigned long long)y << 32) | x;
}
__device__ __forceinline__ void st_rec(unsigned long long* p, float a, float b, uint32_t tag) {
    asm volatile("st.relaxed.gpu.global.b64 [%0], %1;" ::"l"(p), "l"(pack_rec(a, b, tag)) : "memory");
}
__device__ __forceinline__ float rec_lo(unsigned long long w) { return __uint_as_float((uint32_t)w & ~15u); }
__device__ __forceinline__ float rec_hi(unsigned long long w) { return __uint_as_float((uint32_t)(w >> 32) & ~15u); }
__device__ __forceinline__ unsigned long long ld_rec1(const unsigned long long* p) {
    unsigned long long x;
    asm volatile("ld.relaxed.gpu.global.b64 %0, [%1];" : "=l"(x) : "l"(p) : "memory");
    return x;
}
__device__ __forceinline__ void ld_rec2(const unsigned long long* p, unsigned long long& x, unsigned long long& y) {
    asm volatile("ld.relaxed.gpu.global.v2.b64 {%0, %1}, [%2];" : "=l"(x), "=l"(y) : "l"(p) : "memory");
}
__device__ __forceinline__ uint32_t rec_bad(unsigned long long w, uint32_t tlo, uint32_t thi) {
    return (((uint32_t)w ^ tlo) | ((uint32_t)(w >> 32) ^ thi)) & 15u;
}
__device__ __forceinline__ void st_ml(unsigned long long* p, float m, float l, uint32_t tag) {
    const uint32_t y = ((__float_as_uint(l) + 0x80u) & ~0xffu) | tag;
    asm volatile("st.relaxed.gpu.global.b64 [%0], %1;" ::"l"(p), "l"(((unsigned long long)y << 32) | __float_as_uint(m)) : "memory");
}
__device__ __forceinline__ uint32_t ml_bad(unsigned long long w, uint32_t tag) { return ((uint32_t)(w >> 32) ^ tag) & 0xffu; }
__device__ __forceinline__ float ml_m(unsigned long long w) { return __uint_as_float((uint32_t)w); }
__device__ __forceinline__ float ml_l(unsigned long long w) { return __uint_as_float((uint32_t)(w >> 32) & ~0xffu); }
__device__ __forceinline__ float warp_max(float v) {
    const int b = __float_as_int(v);
    const int k = __reduce_max_sync(0xffffffffu, b ^ ((b >> 31) & 0x7fffffff));
    return __int_as_float(k ^ ((k >> 31) & 0x7fffffff));
}
__device__ __forceinline__ uint32_t round_tag(unsigned int epoch, int r) {
    constexpr unsigned kUses = (kRounds + kPR - 1) / kPR;
    return (epoch * kUses + (unsigned)(r / kPR)) % 255u + 1u;
}

__device__ __forceinline__ void rotate_q(uint32_t* qrow, int p, uint32_t c_lo, uint32_t c_hi, uint32_t s_lo, uint32_t s_hi) {
    const uint32_t lo = qrow[p], hi = qrow[p + 48];
    const float a0 = bf_round(bf_lo(lo) * bf_lo(c_lo)) + bf_round(-bf_lo(hi) * bf_lo(s_lo));
    const float a1 = bf_round(bf_hi(lo) * bf_hi(c_lo)) + bf_round(-bf_hi(hi) * bf_hi(s_lo));
    const float b0 = bf_round(bf_lo(hi) * bf_lo(c_hi)) + bf_round(bf_lo(lo) * bf_lo(s_hi));
    const float b1 = bf_round(bf_hi(hi) * bf_hi(c_hi)) + bf_round(bf_hi(lo) * bf_hi(s_hi));
    const __nv_bfloat162 ua = __floats2bfloat162_rn(a0, a1), ub = __floats2bfloat162_rn(b0, b1);
    qrow[p] = *reinterpret_cast<const uint32_t*>(&ua);
    qrow[p + 48] = *reinterpret_cast<const uint32_t*>(&ub);
}
__device__ __forceinline__ int deferred_to(int blk, int r) {
    return (unsigned)(r - kDef0) < (unsigned)kFHeads ? (blk - kF * (r - kDef0)) & (kFHeads - 1) : kF;
}

__device__ __forceinline__ unsigned role_of_sm(unsigned smid) {
    const unsigned u = smid >> 1;
    const unsigned g = u < 32 ? u & 7 : u < 60 ? 1 + (u - 32) % 7 : u < 62 ? u - 54 : 0;
    const unsigned t = u < 32 ? u >> 3 : u < 60 ? 4 + (u - 32) / 7 : u < 62 ? 8 : u - 58;
    const unsigned lin = 16 * g + (g == 7 ? 2 : 0) + 2 * t + (smid & 1);
    if (lin < 2 || lin == 48 || lin == 49) return kStream + (lin & 1) + (lin < 2 ? 0 : 2);
    const unsigned x = lin - (lin < 48 ? 2 : 4);
    return (x & 14) * 8 + (x >> 4) * 2 + (x & 1);
}
static_assert(kGrid == 132 && kTeams == 4, "role_of_sm");
struct Scalars { const __nv_bfloat16* p[4]; };

__global__ void __launch_bounds__(kThreads, 1)
attn_kernel(const __grid_constant__ Scalars scal, const int* __restrict__ qk, int by_sm, const __nv_bfloat16* __restrict__ kcos,
            const __nv_bfloat16* __restrict__ ksin, const int* __restrict__ qv, const __nv_bfloat16* __restrict__ q,
            const __nv_bfloat16* __restrict__ qcos, const __nv_bfloat16* __restrict__ qsin,
            __nv_bfloat16* __restrict__ out, const __grid_constant__ CUtensorMap tmv) {
    extern __shared__ __align__(128) unsigned char smem[];
    const int warp = threadIdx.x >> 5, lane = threadIdx.x & 31;
    const uint32_t full0 = s2u(smem + kOffBar), empty0 = full0 + 2 * kNS * 8;
    const uint32_t sfull = empty0 + 2 * kNS * 8, sempty = sfull + 16, mxbar = sempty + 16, fine = mxbar + 16;
    volatile unsigned int* s_misc = reinterpret_cast<volatile unsigned int*>(smem + kOffMisc);
    uint64_t pol = 0;

    asm volatile("prefetch.global.L2 [%0];"
                 ::"l"(reinterpret_cast<const char*>(qk) + (blockIdx.x * (kThreads / 4) + threadIdx.x / 4) * 128) : "memory");
    unsigned bid = blockIdx.x;
    if (by_sm) {
        unsigned smid, nsm;
        asm volatile("mov.u32 %0, %%smid;" : "=r"(smid));
        asm volatile("mov.u32 %0, %%nsmid;" : "=r"(nsm));
        if (nsm == kGrid) bid = role_of_sm(smid);
    }
    if (threadIdx.x == kCW * 32 && bid < kStream) {
        const int m = bid % kSlots;
        const uint32_t sm0 = s2u(smem);
        asm volatile("cp.async.bulk.prefetch.L2.global [%0], %1;"
                     ::"l"(scal.p[bid & 3] + (bid >> 2) * (kNH * kS * 4 / kStream)), "n"(kNH * kS * 4 / kStream * 2) : "memory");
        for (int i = 0; i < 2 * kNS; i++) mbar_init(full0 + 8 * i, 1);
        asm volatile("fence.mbarrier_init.release.cluster;" ::: "memory");
        asm volatile("createpolicy.fractional.L2::evict_first.b64 %0, 1.0;" : "=l"(pol));
        const int* k0 = qk + (size_t)(bid / kSlots * kS + m * kHRows) * kD;
#pragma unroll
        for (int h = 0; h < 2; h++) {
            mbar_expect(full0 + 16 + 8 * h, kHalf);
            bulk_g2s_stream(sm0 + kChunk + h * kHalf, k0 + h * (kS / 2 * kD), kHalf, full0 + 16 + 8 * h, pol);
        }
#pragma unroll
        for (int h = 0; h < 2; h++) {
            mbar_expect(full0 + 8 * h, kHalf);
            bulk_g2s(sm0 + h * kHalf, kcos + (h * (kS / 2) + m * kHRows) * kD, kHalf / 2, full0 + 8 * h);
            bulk_g2s(sm0 + h * kHalf + kHalf / 2, ksin + (h * (kS / 2) + m * kHRows) * kD, kHalf / 2, full0 + 8 * h);
        }
#pragma unroll
        for (int h = 0; h < 2; h++) {
            mbar_expect(full0 + 32 + 8 * h, kHalf);
            bulk_g2s_stream(sm0 + 2 * kChunk + h * kHalf, k0 + (kTeams * kS + h * (kS / 2)) * kD, kHalf, full0 + 32 + 8 * h, pol);
        }
    }

    if (bid >= kStream) {
        const int team = bid - kStream;
        if (threadIdx.x == 0) s_misc[0] = ld_relaxed(&g_epoch);
        __syncthreads();
        if (threadIdx.x == 0 && atomicAdd(&g_arrive, 1u) == kGrid - 1) { g_arrive = 0u; g_epoch = s_misc[0] + 1u; }
        if (warp >= 3 * kMG) return;
        const int grp = warp / 3, t = threadIdx.x - grp * 96;
        constexpr int kRecBytes = kHeadWords * 8;
        if (t == 0) {
            mbar_init(s2u(smem + kOffBar) + grp * 8, 1);
            asm volatile("fence.mbarrier_init.release.cluster;" ::: "memory");
        }
        asm volatile("bar.sync %0, 96;" ::"r"(3 + grp) : "memory");
        for (int r = grp; r < kRounds; r += kMG) {
            const int g = r % kMG;
            const int tt = threadIdx.x - g * 96, qd = tt % 48, half = tt / 48;
            const uint32_t tag = round_tag(s_misc[0], r);
            const uint32_t tlo = tag & 15u, thi = tag >> 4;
            const unsigned long long* rec = g_rec + (size_t)(r % kPR * kTeams + team) * kHeadWords;
            unsigned long long ml, x[16], y[16];
            {
                const unsigned long long* buf = reinterpret_cast<const unsigned long long*>(smem + g * kRecBytes);
                const uint32_t mb = s2u(smem + kOffBar) + g * 8;
                if (tt < 32) {
                    const int want = r == kRounds - 1 ? kQuick : kSlots;
                    for (int i2 = 0;; i2++) {
                        ml = ld_rec1(rec + kSlots * kRecWords + lane);
                        if (__popc(__ballot_sync(0xffffffffu, ml_bad(ml, tag) == 0)) >= want) break;
                        if (i2 > kSpin) __trap();
                        __nanosleep(r >= kRounds - 2 ? kSleep : 5 * kSleep);
                    }
                    if (tt == 0) {
                        mbar_expect(mb, kRecBytes);
                        bulk_g2s(s2u(buf), rec, kRecBytes, mb);
                    }
                }
                mbar_wait(mb, (r / kMG) & 1);
                ml = buf[kSlots * kRecWords + lane];
#pragma unroll
                for (int i = 0; i < 16; i++) {
                    const ulonglong2 u = *reinterpret_cast<const ulonglong2*>(buf + (half * 16 + i) * kRecWords + 2 * qd);
                    x[i] = u.x; y[i] = u.y;
                }
                const unsigned long long* po = rec + half * 16 * kRecWords + 2 * qd;
                for (int it = 0;; it++) {
                    uint32_t any = ml_bad(ml, tag);
                    if (any) ml = ld_rec1(rec + kSlots * kRecWords + lane);
#pragma unroll
                    for (int i = 0; i < 16; i++) {
                        const uint32_t bad = rec_bad(x[i], tlo, thi) | rec_bad(y[i], tlo, thi);
                        if (bad) ld_rec2(po + i * kRecWords, x[i], y[i]);
                        any |= bad;
                    }
                    if (__all_sync(0xffffffffu, any == 0)) break;
                    if (it > kSpin) __trap();
                }
            }
            const float M = ml_m(ml);
            const float MM = warp_max(M);
            const float w = exp2f(M - MM);
            float LL = w * ml_l(ml);
#pragma unroll
            for (int o = 16; o > 0; o >>= 1) LL += __shfl_xor_sync(0xffffffffu, LL, o);
            float4 a = make_float4(0.f, 0.f, 0.f, 0.f);
#pragma unroll
            for (int i = 0; i < 16; i++) {
                const float wi = __shfl_sync(0xffffffffu, w, half * 16 + i);
                a.x = fmaf(wi, rec_lo(x[i]), a.x);
                a.y = fmaf(wi, rec_hi(x[i]), a.y);
                a.z = fmaf(wi, rec_lo(y[i]), a.z);
                a.w = fmaf(wi, rec_hi(y[i]), a.w);
            }
            float* rb = reinterpret_cast<float*>(smem + kMG * kRecBytes) + (2 * g + ((r / kMG) & 1)) * kD + 4 * qd;
            if (half == 1) *reinterpret_cast<float4*>(rb) = a;
            asm volatile("bar.sync %0, 96;" ::"r"(3 + g) : "memory");
            if (half == 0) {
                const float4 u = *reinterpret_cast<float4*>(rb);
                if ((unsigned)(r - kDef0) < (unsigned)kFHeads) {
                    unsigned long long* pre = g_pre + (size_t)(team * kFHeads + r - kDef0) * kPreWords;
                    const uint32_t ptag = s_misc[0] % 255u + 1u;
                    st_rec(pre + 2 * qd, a.x + u.x, a.y + u.y, ptag);
                    st_rec(pre + 2 * qd + 1, a.z + u.z, a.w + u.w, ptag);
                    if (qd == 0) st_ml(pre + 96, MM, LL, ptag);
                } else {
                    const float inv = __fdividef(1.0f, LL);
                    const __nv_bfloat162 o0 = __floats2bfloat162_rn((a.x + u.x) * inv, (a.y + u.y) * inv);
                    const __nv_bfloat162 o1 = __floats2bfloat162_rn((a.z + u.z) * inv, (a.w + u.w) * inv);
                    uint2 ov;
                    ov.x = *reinterpret_cast<const uint32_t*>(&o0);
                    ov.y = *reinterpret_cast<const uint32_t*>(&o1);
                    *reinterpret_cast<uint2*>(out + (size_t)(kTeams * r + team) * kD + 4 * qd) = ov;
                }
            }
            if (tt == 95)
                asm volatile("st.relaxed.gpu.global.u32 [%0], %1;" ::"l"(&g_mdone[(team * kMG + g) * 32]), "r"(s_misc[0] * kRounds + r + 1) : "memory");
        }
        return;
    }

    const int m = bid % kSlots, team = bid / kSlots;
    const int row0 = m * kHRows;

    if (warp == kCW) {
        unsigned int epoch = 0;
        const size_t off0 = ((size_t)team * kS + row0) * kD;
        const uint32_t sm0 = s2u(smem);
        if (lane == 0) {
            epoch = ld_relaxed(&g_epoch);
            s_misc[0] = epoch;
            s_misc[1] = 0;
            for (int j = 0; j < kNP; j++) {
                s_misc[4 + 2 * j] = epoch * (kStream * (4 * kRounds - 2));
                s_misc[5 + 2 * j] = clock32();
            }
        }
        __syncwarp();
        asm volatile("bar.sync 2, %0;" ::"n"(kThreads) : "memory");
        if (lane == 0) {
            const unsigned int base = epoch * (kStream * (4 * kRounds - 2));
            const int phase = (2 * team - (kTeams - 1)) * (kStream / 2) + (m - kSlots / 2) * kWaveSlot;
            int use0 = kNS, use1 = kNS;
            const int* kp = qk + off0;
            const int* vp = qv + off0;
            for (int ph2 = 4; ph2 < 2 * (2 * kRounds + kF); ph2++) {
                const int p = ph2 >> 1, h = ph2 & 1;
                const bool isv = (p & 1) == 0 || p == 2 * kRounds - 1;
                const int r = p == 2 * kRounds - 1 ? kRounds - 1 : isv ? (p >> 1) - 1 : (p + 1) >> 1;
                const int ramp = max(min(min(ph2 - 4, 4 * kRounds - ph2), kWaveRamp), 0);
                const int tau = kStream * ph2 + (phase + (h ? -kWaveHalf : kWaveHalf) + (isv ? kWaveV : -kWaveV)) * ramp / kWaveRamp;
                const int gone = min(max(tau - kStream * (4 * kDef0 + 3), 0), 4 * kStream * kFHeads) * kF / (2 * kFHeads);
                const unsigned int need = base + tau - gone - max(kRampEnd - ph2, 0) * kRampStep - (p >= 2 * kRounds ? kLeadEnd : kLead);
                const bool skip = isv && deferred_to(4 * h + m / 8, r) < kF;
                const int u = h ? use1 : use0;
                const int slot = u >= kNS ? u - kNS : u;
                const uint32_t dst = sm0 + slot * kChunk + h * kHalf, fullb = full0 + 16 * slot + 8 * h;
                const int* src = (isv ? vp : kp) + (size_t)(r * kTeams * kS + h * (kS / 2)) * kD;
                if (!skip) {
                    const int un = u + 1 == 2 * kNS ? 0 : u + 1;
                    if (h) use1 = un; else use0 = un;
                    mbar_wait(fullb + 2 * kNS * 8, u >= kNS ? 0 : 1);
                    if (p < 2 * kRounds) mbar_expect(fullb, kHalf);
                }
                asm volatile("" ::"l"(src), "r"(dst) : "memory");
                if (!skip)
                    for (int it = 0;; it++) {
                        uint32_t x, tx, y, ty;
                        asm volatile("ld.volatile.shared.v4.u32 {%0, %1, %2, %3}, [%4];"
                                     : "=r"(x), "=r"(tx), "=r"(y), "=r"(ty) : "r"(sm0 + kOffMisc + 16) : "memory");
                        const uint32_t now = clock32();
                        x += min(((now - tx) * kRate) >> 10, kAhead);
                        y += min(((now - ty) * kRate) >> 10, kAhead);
                        if ((int)((x - need) & (y - need)) >= 0) break;
                        if (it > 16 * kSpin) __trap();
                    }
                if (ph2 == 2 * (2 * kRounds + kF) - 1) s_misc[1] = 1;
                if (p >= 2 * kRounds || skip) {
                    const int hi = m / kFG;
                    const int row = (kTeams * (kDef0 + hi) + team) * kS + ((kF * hi + p - 2 * kRounds) & (kFHeads - 1)) * kFRows + h * (kFRows / 2);
                    const uint32_t fb = fine + 8 * (kFBoxes / 2) * (ph2 - 4 * kRounds);
#pragma unroll 1
                    for (int w = 0; w < kFBoxes / 2; w++)
                        asm volatile("{\n.reg .pred p;\nsetp.ne.u32 p, %6, 0;\n"
                                     "@p cp.async.bulk.tensor.2d.shared::cluster.global.tile.mbarrier::complete_tx::bytes.L2::cache_hint [%0], [%1, {%2, %3}], [%4], %5;\n}"
                                     ::"r"(dst + w * (kChunk / kFBoxes)), "l"(&tmv), "r"((m % kFG) * kFW), "r"(row + w * (kFRows / kFBoxes)),
                                       "r"(fb + 8 * w), "l"(pol), "r"((uint32_t)!skip) : "memory");
                } else {
                    bulk_g2s_stream(dst, src, kHalf, fullb, pol);
                }
            }
        }
    } else if (warp >= kCW + 2) {
        asm volatile("bar.sync 2, %0;" ::"n"(kThreads) : "memory");
        if (lane == 0) {
            const int j = warp - (kCW + 2);
            for (int it = 0; !s_misc[1]; it++) {
                const uint32_t t = clock32();
                const uint32_t v = ld_relaxed(prog_counter(j));
                asm volatile("st.volatile.shared.v2.u32 [%0], {%1, %2};" ::"r"(s2u(smem) + kOffMisc + 16 + 8 * j), "r"(v), "r"(t) : "memory");
                if (s_misc[1]) break;
                if (it > kSpin) __trap();
                __nanosleep(kPollSleep);
            }
        }
    } else if (warp == kCW + 1) {
        {
            if (lane < 2 * kNS + 6) mbar_init(empty0 + 8 * lane, lane < 2 * kNS ? kCW / 2 : (lane >= 2 * kNS + 2 && lane < 2 * kNS + 4) ? 1 : kCW);
            asm volatile("fence.mbarrier_init.release.cluster;" ::: "memory");
        }
        asm volatile("bar.sync 2, %0;" ::"n"(kThreads) : "memory");
        const unsigned int epoch = s_misc[0];
        if (lane == 0 && atomicAdd(&g_arrive, 1u) == kGrid - 1) { g_arrive = 0u; g_epoch = epoch + 1u; }
        {
            const uint32_t sm0 = s2u(smem);
            const __nv_bfloat16* src = scal.p[lane >> 3] + (size_t)team * kS + row0 + (lane & 4) * (kS / 8) + (lane & 3) * 8;
            const __nv_bfloat16* qs = q + team * kD + lane * 8;
#pragma unroll 1
            for (int r = kEarly; r < kRounds; r++) {
                cp16(sm0 + kOffScal + r * 512 + lane * 16, src + (size_t)r * (kTeams * kS));
                if (lane < 24) cp16(sm0 + kOffQ + r * (kD * 2) + lane * 16, qs + r * (kTeams * kD));
                if (r == 2 * kEarly - 1 || r == kRounds - 1) asm volatile("cp.async.commit_group;" ::: "memory");
            }
        }
        uint32_t cs[2][4];
#pragma unroll
        for (int i = 0; i < 2; i++) {
            const int p = (lane + 32 * i) % 48;
            cs[i][0] = ld_pair(qcos + 2 * p); cs[i][1] = ld_pair(qcos + 2 * p + 96);
            cs[i][2] = ld_pair(qsin + 2 * p); cs[i][3] = ld_pair(qsin + 2 * p + 96);
        }
        asm volatile("cp.async.wait_group 1;" ::: "memory");
        __syncwarp();
        for (int r = 0; r < kRounds; r++) {
            const float* sc = reinterpret_cast<const float*>(smem + kOffSc) + (r & 1) * (kCW * kScStride);
            const uint32_t tag = round_tag(epoch, r);
            unsigned long long* rec = g_rec + (size_t)(r % kPR * kTeams + team) * kHeadWords;
            if (r >= kEarly && r < kEarly + kF * kFBoxes && lane == 0) {
                mbar_init(fine + 8 * (r - kEarly), 1);
                asm volatile("fence.mbarrier_init.release.cluster;" ::: "memory");
                mbar_expect(fine + 8 * (r - kEarly), kChunk / kFBoxes);
                asm volatile("fence.proxy.async.shared::cta;" ::: "memory");
            }
            if (r == kPrep + m / 2) {
                const unsigned long long* pre = g_pre + (size_t)(team * kFHeads + m / kFG) * kPreWords;
                const unsigned long long* lgp = g_lg + (size_t)(team * kFHeads + m / kFG) * (kF * kFRows);
                const uint32_t ptag = epoch % 255u + 1u;
                unsigned long long ml, po;
                for (int it = 0;; it++) {
                    ml = ld_rec1(pre + 96);
                    po = ld_rec1(pre + (m % kFG) * (kFW / 2) + lane % (kFW / 2));
                    if (!(ml_bad(ml, ptag) | rec_bad(po, ptag & 15u, ptag >> 4))) break;
                    if (it > kSpin) __trap();
                }
                const float inv = 1.0f / ml_l(ml);
                if (lane < kFW / 2) {
                    reinterpret_cast<float2*>(smem + kOffFin)[lane] = make_float2(rec_lo(po) * inv, rec_hi(po) * inv);
                }
#pragma unroll 1
                for (int c = 0; c < kF; c++) {
                    unsigned long long u[8];
                    for (int it = 0;; it++) {
                        uint32_t bad = 0;
#pragma unroll
                        for (int k = 0; k < 8; k++) {
                            u[k] = ld_rec1(lgp + c * kFRows + 32 * k + lane);
                            bad |= ml_bad(u[k], ptag);
                        }
                        if (!bad) break;
                        if (it > kSpin) __trap();
                    }
#pragma unroll
                    for (int k = 0; k < 8; k++)
                        reinterpret_cast<float*>(smem + kOffW)[c * kFRows + 32 * k + lane] = ml_l(u[k]) * exp2f(ml_m(u[k]) - ml_m(ml)) * inv;
                }
                __syncwarp();
            }
            if (r == kRounds - 3 && lane == 0) asm volatile("prefetch.tensormap [%0];" ::"l"(&tmv) : "memory");
            if (r == kEarly) {
                asm volatile("cp.async.wait_all;" ::: "memory");
                __syncwarp();
            }
            if (r + kEarly < kRounds) {
                uint32_t* qrow = reinterpret_cast<uint32_t*>(smem + kOffQ + (r + kEarly) * (kD * 2));
                rotate_q(qrow, lane, cs[0][0], cs[0][1], cs[0][2], cs[0][3]);
                if (lane < 16) rotate_q(qrow, lane + 32, cs[1][0], cs[1][1], cs[1][2], cs[1][3]);
            }
            if (r >= kPR) {
                const unsigned int* mdone = &g_mdone[(team * kMG + r % kMG) * 32];
                const unsigned int need = epoch * kRounds + r - kPR + 1;
                for (int it = 0; (int)(ld_relaxed(mdone) - need) < 0; it++)
                    if (it > kSpin) __trap();
            }
            mbar_wait(sfull + 8 * (r & 1), (r >> 1) & 1);
            const float M = sc[0];
            float L = lane < kCW ? sc[lane * kScStride + 1] : 0.f;
            float acc[2][6];
#pragma unroll
            for (int ww = 0; ww < kCW; ww++) {
#pragma unroll
                for (int j = 0; j < 3; j++) {
                    const float2 t = *reinterpret_cast<const float2*>(sc + ww * kScStride + 4 + 64 * j + 2 * lane);
                    acc[ww & 1][2 * j] = ww < 2 ? t.x : acc[ww & 1][2 * j] + t.x;
                    acc[ww & 1][2 * j + 1] = ww < 2 ? t.y : acc[ww & 1][2 * j + 1] + t.y;
                }
                if ((ww & 3) == 3 && ww < 15) L += __shfl_xor_sync(0xffffffffu, L, 8 >> (ww >> 2));
            }
            L += __shfl_xor_sync(0xffffffffu, L, 1);
#pragma unroll
            for (int j = 0; j < 3; j++)
                st_rec(rec + m * kRecWords + 32 * j + lane, acc[0][2 * j] + acc[1][2 * j], acc[0][2 * j + 1] + acc[1][2 * j + 1], tag);
            if (lane == 0) st_ml(rec + kSlots * kRecWords + m, M, L, tag);
            __syncwarp();
            if (lane == 0) mbar_arrive(sempty + 8 * (r & 1));
        }
    } else {
        int dp[3];
#pragma unroll
        for (int j = 0; j < 3; j++) dp[j] = (64 * j + 2 * lane + 96) % kD;
        {
            const uint32_t sm0 = s2u(smem);
            if (warp < kEarly) {
                cp16(sm0 + kOffScal + threadIdx.x * 16, scal.p[lane >> 3] + (size_t)(kTeams * warp + team) * kS + row0 + (lane & 4) * (kS / 8) + (lane & 3) * 8);
            } else if (warp < 2 * kEarly && lane < 24) {
                cp16(sm0 + kOffQ + (warp - kEarly) * (kD * 2) + lane * 16, q + (size_t)(kTeams * (warp - kEarly) + team) * kD + lane * 8);
            }
            asm volatile("cp.async.commit_group;" ::: "memory");
        }
        const int p = threadIdx.x % 48, g = threadIdx.x / 48;
        const uint32_t c_lo = ld_pair(qcos + 2 * p), c_hi = ld_pair(qcos + 2 * p + 96);
        const uint32_t s_lo = ld_pair(qsin + 2 * p), s_hi = ld_pair(qsin + 2 * p + 96);
        float kc[kR][6], ks[kR][6];
        asm volatile("bar.sync 2, %0;" ::"n"(kThreads) : "memory");
        unsigned int* prog = prog_counter(((m >> 1) ^ (m >> 4) ^ team) & 1);
        const int mute = (m & 1) * 256;
        const int half = warp / (kCW / 2);
        const uint32_t fullh = full0 + 8 * half, emptyh = empty0 + 8 * half;
        mbar_wait(fullh, 0);
#pragma unroll
        for (int i = 0; i < kR; i++) {
            const unsigned char* cb = smem + half * (kHalf / 2) + (warp * kR + i) * (kD * 2);
#pragma unroll
            for (int j = 0; j < 3; j++) {
                const uint32_t uc = *reinterpret_cast<const uint32_t*>(cb + 128 * j + 4 * lane);
                const uint32_t us = *reinterpret_cast<const uint32_t*>(cb + kHalf / 2 + 2 * dp[j]);
                kc[i][2 * j] = bf_lo(uc); kc[i][2 * j + 1] = bf_hi(uc);
                const float sg = (j == 0 || (j == 1 && lane < 16)) ? 1.f : -1.f;
                ks[i][2 * j] = sg * bf_lo(us); ks[i][2 * j + 1] = sg * bf_hi(us);
            }
        }
        __syncwarp();
        if (lane == 0) mbar_arrive(emptyh);
        asm volatile("cp.async.wait_group 0;" ::: "memory");
        asm volatile("bar.sync 1, %0;" ::"n"(kCW * 32) : "memory");
        if (g < kEarly) rotate_q(reinterpret_cast<uint32_t*>(smem + kOffQ + g * (kD * 2)), p, c_lo, c_hi, s_lo, s_hi);
        asm volatile("bar.sync 1, %0;" ::"n"(kCW * 32) : "memory");
        const float scale_log2e = 1.4426950408889634f * rsqrtf((float)kD);
        float* my0 = reinterpret_cast<float*>(smem + kOffSc) + warp * kScStride;

        float* s_max = reinterpret_cast<float*>(smem + kOffMax);
        int slot = 1;
        uint32_t ph = 0;
        float lgc[kR] = {0.f, 0.f, 0.f, 0.f};
        for (int it = 0; it <= kRounds; it++) {
            float lg[kR];
            if (it < kRounds) {
                float qa[6], qb[6];
#pragma unroll
                for (int j = 0; j < 3; j++) {
                    const uint32_t qo = *reinterpret_cast<const uint32_t*>(smem + kOffQ + it * (kD * 2) + 2 * (64 * j + 2 * lane));
                    const uint32_t qp = *reinterpret_cast<const uint32_t*>(smem + kOffQ + it * (kD * 2) + 2 * dp[j]);
                    qa[2 * j] = bf_lo(qo); qa[2 * j + 1] = bf_hi(qo);
                    qb[2 * j] = bf_lo(qp); qb[2 * j + 1] = bf_hi(qp);
                }
                const unsigned char* sp = smem + kOffScal + it * (4 * kRows * 2) + warp * (kR * 2);
                const uint2 uks = *reinterpret_cast<const uint2*>(sp);
                const uint2 ukz = *reinterpret_cast<const uint2*>(sp + kRows * 2);
                const float kz[4] = {bf_lo(ukz.x), bf_hi(ukz.x), bf_lo(ukz.y), bf_hi(ukz.y)};
                const float sk[4] = {bf_lo(uks.x), bf_hi(uks.x), bf_lo(uks.y), bf_hi(uks.y)};
                mbar_wait(fullh + 16 * slot, ph);
                if ((threadIdx.x & 255) == mute) asm volatile("red.relaxed.gpu.global.add.u32 [%0], %1;" ::"l"(prog), "n"(kSample) : "memory");
                const unsigned char* kb = smem + slot * kChunk + warp * (kR * kRowBytes) + lane * 8;
#pragma unroll
                for (int i = 0; i < kR; i++) {
                    float dot = 0.f;
#pragma unroll
                    for (int j = 0; j < 3; j++) {
                        const int2 kk = *reinterpret_cast<const int2*>(kb + i * kRowBytes + 256 * j);
                        const float e0 = qa[2 * j] * kc[i][2 * j] + qb[2 * j] * ks[i][2 * j];
                        const float e1 = qa[2 * j + 1] * kc[i][2 * j + 1] + qb[2 * j + 1] * ks[i][2 * j + 1];
                        dot = fmaf((float)kk.x - kz[i], e0, dot);
                        dot = fmaf((float)kk.y - kz[i], e1, dot);
                    }
                    lg[i] = dot;
                }
                __syncwarp();
                if (lane == 0) mbar_arrive(emptyh + 16 * slot);
                if (++slot == kNS) { slot = 0; ph ^= 1; }
#pragma unroll
                for (int o = 16; o > 0; o >>= 1) {
#pragma unroll
                    for (int i = 0; i < kR; i++) lg[i] += __shfl_xor_sync(0xffffffffu, lg[i], o);
                }
                float mw = -INFINITY;
#pragma unroll
                for (int i = 0; i < kR; i++) {
                    lg[i] = lg[i] * sk[i] * scale_log2e;
                    mw = fmaxf(mw, lg[i]);
                }
                if (lane == 0) {
                    s_max[(it & 3) * kCW + warp] = mw;
                    mbar_arrive(mxbar + 8 * (it & 1));
                }
            }
            if (it > 0) {
                const int r = it - 1;
                float* my = my0 + (r & 1) * (kCW * kScStride);
                const int df = deferred_to(4 * half + m / 8, r);
                const unsigned char* sp = smem + kOffScal + r * (4 * kRows * 2) + warp * (kR * 2);
                const uint2 uvs = *reinterpret_cast<const uint2*>(sp + 2 * kRows * 2);
                const uint2 uvz = *reinterpret_cast<const uint2*>(sp + 3 * kRows * 2);
                const float vz[4] = {bf_lo(uvz.x), bf_hi(uvz.x), bf_lo(uvz.y), bf_hi(uvz.y)};
                const float sv[4] = {bf_lo(uvs.x), bf_hi(uvs.x), bf_lo(uvs.y), bf_hi(uvs.y)};
                mbar_wait(mxbar + 8 * (r & 1), (r >> 1) & 1);
                float M;
                {
                    const float4* pm4 = reinterpret_cast<const float4*>(s_max + (r & 3) * kCW);
                    const float4 m0 = pm4[0], m1 = pm4[1], m2 = pm4[2], m3 = pm4[3];
                    M = fmaxf(fmaxf(fmaxf(fmaxf(m0.x, m0.y), fmaxf(m0.z, m0.w)), fmaxf(fmaxf(m1.x, m1.y), fmaxf(m1.z, m1.w))),
                              fmaxf(fmaxf(fmaxf(m2.x, m2.y), fmaxf(m2.z, m2.w)), fmaxf(fmaxf(m3.x, m3.y), fmaxf(m3.z, m3.w))));
                }
                float lw = 0.f, cz = 0.f, pv[kR];
#pragma unroll
                for (int i = 0; i < kR; i++) {
                    const float p = exp2f(lgc[i] - M);
                    lw += p;
                    pv[i] = p * sv[i];
                    cz = fmaf(pv[i], vz[i], cz);
                }
                mbar_wait(sempty + 8 * (r & 1), ((r >> 1) & 1) ^ 1);
                if (lane == 0) { my[0] = M; my[1] = lw; }
                float acc[6] = {-cz, -cz, -cz, -cz, -cz, -cz};
                if (df < kF) {
                    if (lane < kR)
                        st_ml(g_lg + ((team * kFHeads + r - kDef0) * kF + df) * kFRows + (m % 8) * kHRows + (warp % 8) * kR + lane, M,
                              lane == 0 ? pv[0] : lane == 1 ? pv[1] : lane == 2 ? pv[2] : pv[3], s_misc[0] % 255u + 1u);
                } else {
                    mbar_wait(fullh + 16 * slot, ph);
                    if ((threadIdx.x & 255) == mute) asm volatile("red.relaxed.gpu.global.add.u32 [%0], %1;" ::"l"(prog), "n"(kSample) : "memory");
                    const unsigned char* vb = smem + slot * kChunk + warp * (kR * kRowBytes) + lane * 8;
#pragma unroll
                    for (int i = 0; i < kR; i++) {
#pragma unroll
                        for (int j = 0; j < 3; j++) {
                            const int2 vv = *reinterpret_cast<const int2*>(vb + i * kRowBytes + 256 * j);
                            acc[2 * j] = fmaf(pv[i], (float)vv.x, acc[2 * j]);
                            acc[2 * j + 1] = fmaf(pv[i], (float)vv.y, acc[2 * j + 1]);
                        }
                    }
                    __syncwarp();
                    if (lane == 0) mbar_arrive(emptyh + 16 * slot);
                    if (++slot == kNS) { slot = 0; ph ^= 1; }
                }
#pragma unroll
                for (int j = 0; j < 3; j++)
                    *reinterpret_cast<float2*>(my + 4 + 64 * j + 2 * lane) = make_float2(acc[2 * j], acc[2 * j + 1]);
                __syncwarp();
                if (lane == 0) mbar_arrive(sfull + 8 * (r & 1));
            }
#pragma unroll
            for (int i = 0; i < kR; i++) lgc[i] = lg[i];
        }
        {
            const int cp = lane < kFW / 2 ? lane : 0;
            const int ft = threadIdx.x < kFW ? threadIdx.x : 0;
            const float fin = reinterpret_cast<const float*>(smem + kOffFin)[ft];
            __nv_bfloat16* op = out + (size_t)(kTeams * (kDef0 + m / kFG) + team) * kD + (m % kFG) * kFW + ft;
            float a0 = 0.f, a1 = 0.f, b0 = 0.f, b1 = 0.f;
#pragma unroll 1
            for (int f = 0; f < kF; f++) {
                const float* sw = reinterpret_cast<const float*>(smem + kOffW) + f * kFRows + (warp >> 2) * 16 + (warp & 3) * 4;
                const unsigned char* vb = smem + slot * kChunk + ((warp >> 2) * 16 + (warp & 3) * 4) * (kFW * 4) + cp * 8;
                const uint32_t fb = fine + (f * kFBoxes + (warp >> 2)) * 8;
                float* part = reinterpret_cast<float*>(smem + kOffPart) + f * kPartSize;
                float4 w[4];
#pragma unroll
                for (int k = 0; k < 4; k++) w[k] = *reinterpret_cast<const float4*>(sw + 64 * k);
#pragma unroll
                for (int k = 0; k < 4; k++) {
                    mbar_wait(fb + 32 * k, 0);
                    if ((k & 1) && threadIdx.x == kCW * 32 - 32 + mute && f < kF - 1) asm volatile("red.relaxed.gpu.global.add.u32 [%0], %1;" ::"l"(prog), "n"(kSample) : "memory");
                    const int2 v0 = *reinterpret_cast<const int2*>(vb + k * (64 * kFW * 4));
                    const int2 v1 = *reinterpret_cast<const int2*>(vb + k * (64 * kFW * 4) + kFW * 4);
                    const int2 v2 = *reinterpret_cast<const int2*>(vb + k * (64 * kFW * 4) + 2 * kFW * 4);
                    const int2 v3 = *reinterpret_cast<const int2*>(vb + k * (64 * kFW * 4) + 3 * kFW * 4);
                    a0 = fmaf(w[k].x, (float)v0.x, a0); a1 = fmaf(w[k].x, (float)v0.y, a1);
                    b0 = fmaf(w[k].y, (float)v1.x, b0); b1 = fmaf(w[k].y, (float)v1.y, b1);
                    a0 = fmaf(w[k].z, (float)v2.x, a0); a1 = fmaf(w[k].z, (float)v2.y, a1);
                    b0 = fmaf(w[k].w, (float)v3.x, b0); b1 = fmaf(w[k].w, (float)v3.y, b1);
                }
                if (lane < kFW / 2) {
                    part[lane * kPartStride + warp] = a0 + b0;
                    part[kPartOdd + lane * kPartStride + warp] = a1 + b1;
                }
                if (warp >= 2) {
                    asm volatile("bar.arrive %0, %1;" ::"r"(3 + f), "n"(kCW * 32) : "memory");
                } else {
                    asm volatile("bar.sync %0, %1;" ::"r"(3 + f), "n"(kCW * 32) : "memory");
                    const float4* ps = reinterpret_cast<const float4*>(part + (ft & 1) * kPartOdd + (ft >> 1) * kPartStride);
                    const float4 p0 = ps[0], p1 = ps[1], p2 = ps[2], p3 = ps[3];
                    const float sum = (((p0.x + p0.y) + (p0.z + p0.w)) + ((p1.x + p1.y) + (p1.z + p1.w))) +
                                      (((p2.x + p2.y) + (p2.z + p2.w)) + ((p3.x + p3.y) + ((p3.z + p3.w) + fin)));
                    asm volatile("{\n.reg .pred p;\n.reg .b16 h;\nsetp.ne.u32 p, %2, 0;\ncvt.rn.bf16.f32 h, %1;\n@p st.global.b16 [%0], h;\n}"
                                 ::"l"(op), "f"(sum), "r"((uint32_t)(f == kF - 1 && threadIdx.x < kFW)) : "memory");
                }
                if (++slot == kNS) slot = 0;
            }
        }
    }
}

__global__ void __launch_bounds__(256)
attn_fallback(const __nv_bfloat16* __restrict__ q, const int* __restrict__ qk,
              const __nv_bfloat16* __restrict__ ksc, const __nv_bfloat16* __restrict__ kzp,
              const int* __restrict__ qv, const __nv_bfloat16* __restrict__ vsc,
              const __nv_bfloat16* __restrict__ vzp, const __nv_bfloat16* __restrict__ qcos,
              const __nv_bfloat16* __restrict__ qsin, const __nv_bfloat16* __restrict__ kcos,
              const __nv_bfloat16* __restrict__ ksin, __nv_bfloat16* __restrict__ out) {
    __shared__ float qr[kD], lg[kS], red[8];
    const int h = blockIdx.x, t = threadIdx.x, warp = t >> 5, lane = t & 31;
    if (t < kD) {
        const float x = __bfloat162float(q[h * kD + t]);
        const float y = t < kD / 2 ? -__bfloat162float(q[h * kD + t + kD / 2]) : __bfloat162float(q[h * kD + t - kD / 2]);
        qr[t] = bf_round(bf_round(x * __bfloat162float(qcos[t])) + bf_round(y * __bfloat162float(qsin[t])));
    }
    __syncthreads();
    const float scale_log2e = 1.4426950408889634f * rsqrtf((float)kD);
    float mw = -INFINITY;
    for (int s = warp; s < kS; s += 8) {
        const size_t row = (size_t)h * kS + s;
        const float z = __bfloat162float(kzp[row]);
        float dot = 0.f;
        for (int d = lane; d < kD; d += 32) {
            const int dp = d < kD / 2 ? d + kD / 2 : d - kD / 2;
            const float sn = __bfloat162float(ksin[s * kD + dp]);
            const float e = qr[d] * __bfloat162float(kcos[s * kD + d]) + qr[dp] * (d < kD / 2 ? sn : -sn);
            dot = fmaf((float)qk[row * kD + d] - z, e, dot);
        }
        for (int o = 16; o > 0; o >>= 1) dot += __shfl_xor_sync(0xffffffffu, dot, o);
        dot = dot * __bfloat162float(ksc[row]) * scale_log2e;
        if (lane == 0) lg[s] = dot;
        mw = fmaxf(mw, dot);
    }
    if (lane == 0) red[warp] = mw;
    __syncthreads();
    float M = red[0];
    for (int i = 1; i < 8; i++) M = fmaxf(M, red[i]);
    __syncthreads();
    float l = 0.f;
    for (int s = t; s < kS; s += 256) { const float p = exp2f(lg[s] - M); l += p; lg[s] = p; }
    for (int o = 16; o > 0; o >>= 1) l += __shfl_xor_sync(0xffffffffu, l, o);
    if (lane == 0) red[warp] = l;
    __syncthreads();
    float L = 0.f;
    for (int i = 0; i < 8; i++) L += red[i];
    if (t < kD) {
        float acc = 0.f;
        for (int s = 0; s < kS; s++) {
            const size_t row = (size_t)h * kS + s;
            acc = fmaf(lg[s] * __bfloat162float(vsc[row]), (float)qv[row * kD + t] - __bfloat162float(vzp[row]), acc);
        }
        out[h * kD + t] = __float2bfloat16_rn(acc / L);
    }
}

}

#include <stdio.h>
#include <math.h>
__device__ float g_sig[400 * 10];
__global__ void probe_k(const char* a, int np) {
    unsigned smid; asm volatile("mov.u32 %0, %%smid;" : "=r"(smid));
    if (smid != 10 || (threadIdx.x & 31)) return;
    const int w = threadIdx.x >> 5;
    for (int pg = 0; pg < np; pg++) {
        unsigned sum = 0;
        for (int i = 0; i < 64; i++) {
            const char* p = a + (size_t)pg * 2097152 + w * 131072 + i * 1024;
            unsigned best = ~0u;
            for (int r = 0; r < 4; r++) { unsigned c1, c2, v;
                asm volatile("mov.u32 %0, %%clock;" : "=r"(c1) :: "memory");
                asm volatile("ld.relaxed.gpu.global.u32 %0, [%1];" : "=r"(v) : "l"(p) : "memory");
                asm volatile("{\n.reg .pred p;\nsetp.eq.u32 p, %1, 0x12345678;\n@p trap;\nmov.u32 %0, %%clock;\n}" : "=r"(c2) : "r"(v) : "memory");
                if (r) best = min(best, c2 - c1); }
            sum += best;
        }
        g_sig[pg * 10 + w] = sum / 64.f;
    }
}
static void probe_pages(const char* name, const void* ptr, int np) {
    cudaFuncSetAttribute(probe_k, cudaFuncAttributeMaxDynamicSharedMemorySize, 200000);
    probe_k<<<132, 320, 200000>>>((const char*)ptr, np); cudaDeviceSynchronize();
    static float h[4000]; cudaMemcpyFromSymbol(h, g_sig, sizeof(h));
    fprintf(stderr, "PROBE %s page0:", name); for (int u = 0; u < 10; u++) fprintf(stderr, " %.1f", h[u]); fprintf(stderr, "\nPROBE %s argmax-minus-expected:", name);
    for (int pg = 0; pg < np; pg++) { int b = 0; float bv = -1; for (int u = 0; u < 5; u++) { float v = h[pg * 10 + u] + h[pg * 10 + u + 5]; if (v > bv) { bv = v; b = u; } } fprintf(stderr, "%d", (b + pg) % 5); }
    fprintf(stderr, "\n");
}
extern "C" void kernel_launch(void* const* d_in, const int* in_sizes, int n_in, void* d_out, int out_size) {
    const __nv_bfloat16* q = (const __nv_bfloat16*)d_in[0];
    const int* qk = (const int*)d_in[1];
    const __nv_bfloat16* ksc = (const __nv_bfloat16*)d_in[2];
    const __nv_bfloat16* kzp = (const __nv_bfloat16*)d_in[3];
    const int* qv = (const int*)d_in[4];
    const __nv_bfloat16* vsc = (const __nv_bfloat16*)d_in[5];
    const __nv_bfloat16* vzp = (const __nv_bfloat16*)d_in[6];
    const __nv_bfloat16* qcos = (const __nv_bfloat16*)d_in[7];
    const __nv_bfloat16* qsin = (const __nv_bfloat16*)d_in[8];
    const __nv_bfloat16* kcos = (const __nv_bfloat16*)d_in[9];
    const __nv_bfloat16* ksin = (const __nv_bfloat16*)d_in[10];

    typedef CUresult (*EncodeFn)(CUtensorMap*, CUtensorMapDataType, cuuint32_t, void*, const cuuint64_t*, const cuuint64_t*,
                                 const cuuint32_t*, const cuuint32_t*, CUtensorMapInterleave, CUtensorMapSwizzle,
                                 CUtensorMapL2promotion, CUtensorMapFloatOOBfill);
    static EncodeFn encode = nullptr;
    static int by_sm = 0;
    static int mode = 0;
    if (!mode) {
        int dev = 0, sms = 0, occ = 0;
        cudaGetDevice(&dev);
        cudaDeviceGetAttribute(&sms, cudaDevAttrMultiProcessorCount, dev);
        cudaError_t e = cudaFuncSetAttribute(attn_kernel, cudaFuncAttributeMaxDynamicSharedMemorySize, kSmemBytes);
        if (e == cudaSuccess) e = cudaOccupancyMaxActiveBlocksPerMultiprocessor(&occ, attn_kernel, kThreads, kSmemBytes);
        void* fn = nullptr;
        cudaDriverEntryPointQueryResult qr;
        if (e == cudaSuccess) e = cudaGetDriverEntryPoint("cuTensorMapEncodeTiled", &fn, cudaEnableDefault, &qr);
        encode = (EncodeFn)fn;
        mode = (e == cudaSuccess && fn && occ * sms >= kGrid) ? 1 : 2;
        (void)cudaGetLastError();
        by_sm = sms == kGrid && occ == 1;
    }
    { static int once = 0; if (!once) { once = 1; probe_pages("K", qk, 192); probe_pages("V", qv, 192); } }
    CUtensorMap tmv;
    bool fast = mode == 1;
    if (fast) {
        const cuuint64_t dims[2] = {(cuuint64_t)kD, (cuuint64_t)kNH * kS}, strides[1] = {(cuuint64_t)kRowBytes};
        const cuuint32_t box[2] = {(cuuint32_t)kFW, (cuuint32_t)(kFRows / kFBoxes)}, es[2] = {1, 1};
        fast = encode(&tmv, CU_TENSOR_MAP_DATA_TYPE_INT32, 2, (void*)qv, dims, strides, box, es, CU_TENSOR_MAP_INTERLEAVE_NONE,
                      CU_TENSOR_MAP_SWIZZLE_NONE, CU_TENSOR_MAP_L2_PROMOTION_L2_128B, CU_TENSOR_MAP_FLOAT_OOB_FILL_NONE) == CUDA_SUCCESS;
    }
    if (fast)
        attn_kernel<<<kGrid, kThreads, kSmemBytes>>>(Scalars{{ksc, kzp, vsc, vzp}}, qk, by_sm, kcos, ksin, qv, q, qcos, qsin,
                                                     (__nv_bfloat16*)d_out, tmv);
    else
        attn_fallback<<<kNH, 256>>>(q, qk, ksc, kzp, qv, vsc, vzp, qcos, qsin, kcos, ksin, (__nv_bfloat16*)d_out);
}
```

```cpp
#include <cuda_runtime.h>
#include <cuda.h>
#include <cuda_bf16.h>
#include <stdint.h>

namespace {

constexpr int kB = 8, kH = 32, kS = 2048, kD = 192;
constexpr int kNH = kB * kH;
constexpr int kTeams = 4;
constexpr int kSlots = 32;
constexpr int kRows = kS / kSlots;
constexpr int kRounds = kNH / kTeams;
constexpr int kStream = kTeams * kSlots;
constexpr int kGrid = kStream + kTeams;
constexpr int kCW = 16;
constexpr int kR = kRows / kCW;
constexpr int kNP = 2;
constexpr int kThreads = (kCW + 2 + kNP) * 32;
constexpr int kRowBytes = kD * 4;
constexpr int kChunk = kRows * kRowBytes;
constexpr int kNS = 3;
constexpr int kHalf = kChunk / 2;
constexpr int kHRows = kRows / 2;
constexpr int kLead = 215;
constexpr int kLeadEnd = 250, kBoxStep = 14;
constexpr int kRampEnd = 12, kRampStep = 70;
constexpr int kWaveSlot = 2, kWaveHalf = 32, kWaveRamp = 8;
constexpr int kBlock8 = 160, kBurst = 5;
constexpr int kOriginK = 1 * 32, kOriginV = 4 * 32;
constexpr int kWaveV = ((20 * kBlock8 - 3 * 6 * kStream - 2 * (kOriginV - kOriginK)) % (2 * kBlock8) - kBlock8) / 6;
constexpr uint32_t kRate = 69, kAhead = 256;
constexpr int kSample = 4;
constexpr int kPollSleep = 300;
constexpr int kQuick = 20;
constexpr int kSleep = 200;
constexpr int kPR = 12;
constexpr int kScStride = 196;
constexpr int kOffScal = kNS * kChunk;
constexpr int kOffQ = kOffScal + kRounds * 4 * kRows * 2;
constexpr int kOffSc = kOffQ + kRounds * kD * 2;
constexpr int kOffBar = kOffSc + 2 * kCW * kScStride * 4;
constexpr int kF = 3;
constexpr int kFG = 4;
constexpr int kFW = kD / kFG;
constexpr int kFRows = kRows * kFG;
constexpr int kFHeads = kSlots / kFG;
constexpr int kDef0 = 16;
constexpr int kEarly = 4;
constexpr int kFBoxes = 16;
constexpr int kPrep = 40;
constexpr int kOffW = kOffScal;
constexpr int kOffFin = kOffW + kF * kFRows * 4;
constexpr int kPartStride = 20, kPartOdd = (kFW / 2) * kPartStride + 16, kPartSize = 2 * kPartOdd;
constexpr int kOffPart = kOffFin + kFW * 4;
constexpr int kOffMisc = kOffBar + (4 * kNS + 6 + kF * kFBoxes) * 8;
constexpr int kOffMax = kOffMisc + 32;
constexpr int kSmemBytes = kOffMax + 4 * kCW * 4;
constexpr int kRecWords = kD / 2;
constexpr int kHeadWords = kSlots * (kRecWords + 1);
constexpr int kPreWords = 112;
constexpr int kMG = 6;
static_assert(kNS >= 3, "ring");
static_assert(kOffBar % 8 == 0 && kOffSc % 16 == 0 && kOffMax % 16 == 0, "alignment");
static_assert(kPR % kMG == 0, "ring");
static_assert(kNP == 2 && kOffMisc % 16 == 0 && kLeadEnd - (kFBoxes / 2 - 1) * kBoxStep >= kStream && kS == kFHeads * kFRows && kFHeads == 8, "schedule");
static_assert(kSmemBytes <= 232448, "smem");
static_assert(kDef0 + kFHeads < kPrep && kPrep + 16 + 3 < kRounds && kEarly + kF * kFBoxes + 3 < kRounds && kOffPart <= kOffScal + (kPrep - 2) * 4 * kRows * 2 &&
              kOffPart + kF * kPartSize * 4 <= kOffScal + (kRounds - 2) * 4 * kRows * 2 && kF <= kNS && kFBoxes == kCW, "deferred rounds");

__device__ __align__(128) unsigned long long g_rec[kPR * kTeams * kHeadWords];
__device__ __align__(128) unsigned long long g_pre[kTeams * kFHeads * kPreWords];
__device__ __align__(128) unsigned long long g_lg[kTeams * kFHeads * kF * kFRows];
__device__ unsigned int g_prog[(16384 + 8192) / 4 + 1];
__device__ __align__(128) unsigned int g_epoch;
__device__ __align__(128) unsigned int g_arrive;
__device__ __align__(128) unsigned int g_mdone[kTeams * kMG * 32];

constexpr int kSpin = 1 << 24;

__device__ __forceinline__ uint32_t clock32() {
    uint32_t t;
    asm volatile("mov.u32 %0, %%clock;" : "=r"(t)::"memory");
    return t;
}
__device__ __forceinline__ unsigned int* prog_counter(int j) {
    return reinterpret_cast<unsigned int*>(((reinterpret_cast<uintptr_t>(g_prog) + 16383) & ~(uintptr_t)16383) + 8192 * j);
}
__device__ __forceinline__ uint32_t s2u(const void* p) { return (uint32_t)__cvta_generic_to_shared(p); }
__device__ __forceinline__ void mbar_init(uint32_t a, int c) {
    asm volatile("mbarrier.init.shared::cta.b64 [%0], %1;" ::"r"(a), "r"(c));
}
__device__ __forceinline__ void mbar_wait(uint32_t a, uint32_t ph) {
    uint32_t ok;
    for (int it = 0;; it++) {
        asm volatile(
            "{\n.reg .pred p;\nmbarrier.try_wait.parity.shared::cta.b64 p, [%1], %2;\nselp.u32 %0, 1, 0, p;\n}"
            : "=r"(ok) : "r"(a), "r"(ph) : "memory");
        if (ok) break;
        if (it > kSpin) __trap();
    }
}
__device__ __forceinline__ void mbar_arrive(uint32_t a) {
    asm volatile("mbarrier.arrive.shared::cta.b64 _, [%0];" ::"r"(a) : "memory");
}
__device__ __forceinline__ void mbar_expect(uint32_t a, uint32_t bytes) {
    asm volatile("mbarrier.arrive.expect_tx.shared::cta.b64 _, [%0], %1;" ::"r"(a), "r"(bytes) : "memory");
}
__device__ __forceinline__ void bulk_g2s_stream(uint32_t dst, const void* src, uint32_t bytes, uint32_t mbar, uint64_t pol) {
    asm volatile("cp.async.bulk.shared::cluster.global.mbarrier::complete_tx::bytes.L2::cache_hint [%0], [%1], %2, [%3], %4;"
                 ::"r"(dst), "l"(src), "r"(bytes), "r"(mbar), "l"(pol) : "memory");
}
__device__ __forceinline__ void bulk_g2s(uint32_t dst, const void* src, uint32_t bytes, uint32_t mbar) {
    asm volatile("cp.async.bulk.shared::cluster.global.mbarrier::complete_tx::bytes [%0], [%1], %2, [%3];"
                 ::"r"(dst), "l"(src), "r"(bytes), "r"(mbar) : "memory");
}
__device__ __forceinline__ void cp16(uint32_t dst, const void* src) {
    asm volatile("cp.async.cg.shared.global [%0], [%1], 16;" ::"r"(dst), "l"(src) : "memory");
}
__device__ __forceinline__ float bf_lo(uint32_t u) { return __uint_as_float(u << 16); }
__device__ __forceinline__ float bf_hi(uint32_t u) { return __uint_as_float(u & 0xffff0000u); }
__device__ __forceinline__ float bf_round(float x) { return __bfloat162float(__float2bfloat16_rn(x)); }
__device__ __forceinline__ uint32_t ld_pair(const __nv_bfloat16* p) {
    return __ldg(reinterpret_cast<const uint32_t*>(p));
}
__device__ __forceinline__ unsigned int ld_relaxed(const unsigned int* p) {
    unsigned int v;
    asm volatile("ld.relaxed.gpu.global.u32 %0, [%1];" : "=r"(v) : "l"(p) : "memory");
    return v;
}
__device__ __forceinline__ unsigned long long pack_rec(float a, float b, uint32_t tag) {
    const uint32_t x = (__float_as_uint(a) & ~15u) | (tag & 15u), y = (__float_as_uint(b) & ~15u) | (tag >> 4);
    return ((unsigned long long)y << 32) | x;
}
__device__ __forceinline__ void st_rec(unsigned long long* p, float a, float b, uint32_t tag) {
    asm volatile("st.relaxed.gpu.global.b64 [%0], %1;" ::"l"(p), "l"(pack_rec(a, b, tag)) : "memory");
}
__device__ __forceinline__ float rec_lo(unsigned long long w) { return __uint_as_float((uint32_t)w & ~15u); }
__device__ __forceinline__ float rec_hi(unsigned long long w) { return __uint_as_float((uint32_t)(w >> 32) & ~15u); }
__device__ __forceinline__ unsigned long long ld_rec1(const unsigned long long* p) {
    unsigned long long x;
    asm volatile("ld.relaxed.gpu.global.b64 %0, [%1];" : "=l"(x) : "l"(p) : "memory");
    return x;
}
__device__ __forceinline__ void ld_rec2(const unsigned long long* p, unsigned long long& x, unsigned long long& y) {
    asm volatile("ld.relaxed.gpu.global.v2.b64 {%0, %1}, [%2];" : "=l"(x), "=l"(y) : "l"(p) : "memory");
}
__device__ __forceinline__ uint32_t rec_bad(unsigned long long w, uint32_t tlo, uint32_t thi) {
    return (((uint32_t)w ^ tlo) | ((uint32_t)(w >> 32) ^ thi)) & 15u;
}
__device__ __forceinline__ void st_ml(unsigned long long* p, float m, float l, uint32_t tag) {
    const uint32_t y = ((__float_as_uint(l) + 0x80u) & ~0xffu) | tag;
    asm volatile("st.relaxed.gpu.global.b64 [%0], %1;" ::"l"(p), "l"(((unsigned long long)y << 32) | __float_as_uint(m)) : "memory");
}
__device__ __forceinline__ uint32_t ml_bad(unsigned long long w, uint32_t tag) { return ((uint32_t)(w >> 32) ^ tag) & 0xffu; }
__device__ __forceinline__ float ml_m(unsigned long long w) { return __uint_as_float((uint32_t)w); }
__device__ __forceinline__ float ml_l(unsigned long long w) { return __uint_as_float((uint32_t)(w >> 32) & ~0xffu); }
__device__ __forceinline__ float warp_max(float v) {
    const int b = __float_as_int(v);
    const int k = __reduce_max_sync(0xffffffffu, b ^ ((b >> 31) & 0x7fffffff));
    return __int_as_float(k ^ ((k >> 31) & 0x7fffffff));
}
__device__ __forceinline__ uint32_t round_tag(unsigned int epoch, int r) {
    constexpr unsigned kUses = (kRounds + kPR - 1) / kPR;
    return (epoch * kUses + (unsigned)(r / kPR)) % 255u + 1u;
}

__device__ __forceinline__ void rotate_q(uint32_t* qrow, int p, uint32_t c_lo, uint32_t c_hi, uint32_t s_lo, uint32_t s_hi) {
    const uint32_t lo = qrow[p], hi = qrow[p + 48];
    const float a0 = bf_round(bf_lo(lo) * bf_lo(c_lo)) + bf_round(-bf_lo(hi) * bf_lo(s_lo));
    const float a1 = bf_round(bf_hi(lo) * bf_hi(c_lo)) + bf_round(-bf_hi(hi) * bf_hi(s_lo));
    const float b0 = bf_round(bf_lo(hi) * bf_lo(c_hi)) + bf_round(bf_lo(lo) * bf_lo(s_hi));
    const float b1 = bf_round(bf_hi(hi) * bf_hi(c_hi)) + bf_round(bf_hi(lo) * bf_hi(s_hi));
    const __nv_bfloat162 ua = __floats2bfloat162_rn(a0, a1), ub = __floats2bfloat162_rn(b0, b1);
    qrow[p] = *reinterpret_cast<const uint32_t*>(&ua);
    qrow[p + 48] = *reinterpret_cast<const uint32_t*>(&ub);
}
__device__ __forceinline__ int deferred_to(int blk, int r) {
    return (unsigned)(r - kDef0) < (unsigned)kFHeads ? (blk - kF * (r - kDef0)) & (kFHeads - 1) : kF;
}

__device__ __forceinline__ unsigned role_of_sm(unsigned smid) {
    const unsigned u = smid >> 1;
    const unsigned g = u < 32 ? u & 7 : u < 60 ? 1 + (u - 32) % 7 : u < 62 ? u - 54 : 0;
    const unsigned t = u < 32 ? u >> 3 : u < 60 ? 4 + (u - 32) / 7 : u < 62 ? 8 : u - 58;
    const unsigned lin = 16 * g + (g == 7 ? 2 : 0) + 2 * t + (smid & 1);
    if (lin < 2 || lin == 48 || lin == 49) return kStream + (lin & 1) + (lin < 2 ? 0 : 2);
    const unsigned x = lin - (lin < 48 ? 2 : 4);
    return (x & 14) * 8 + (x >> 4) * 2 + (x & 1);
}
static_assert(kGrid == 132 && kTeams == 4, "role_of_sm");
struct Scalars { const __nv_bfloat16* p[4]; };

__global__ void __launch_bounds__(kThreads, 1)
attn_kernel(const __grid_constant__ Scalars scal, const int* __restrict__ qk, int by_sm, const __nv_bfloat16* __restrict__ kcos,
            const __nv_bfloat16* __restrict__ ksin, const int* __restrict__ qv, const __nv_bfloat16* __restrict__ q,
            const __nv_bfloat16* __restrict__ qcos, const __nv_bfloat16* __restrict__ qsin,
            __nv_bfloat16* __restrict__ out, const __grid_constant__ CUtensorMap tmv) {
    extern __shared__ __align__(128) unsigned char smem[];
    const int warp = threadIdx.x >> 5, lane = threadIdx.x & 31;
    const uint32_t full0 = s2u(smem + kOffBar), empty0 = full0 + 2 * kNS * 8;
    const uint32_t sfull = empty0 + 2 * kNS * 8, sempty = sfull + 16, mxbar = sempty + 16, fine = mxbar + 16;
    volatile unsigned int* s_misc = reinterpret_cast<volatile unsigned int*>(smem + kOffMisc);
    uint64_t pol = 0;

    asm volatile("prefetch.global.L2 [%0];"
                 ::"l"(reinterpret_cast<const char*>(qk) + (blockIdx.x * (kThreads / 4) + threadIdx.x / 4) * 128) : "memory");
    unsigned bid = blockIdx.x;
    if (by_sm) {
        unsigned smid, nsm;
        asm volatile("mov.u32 %0, %%smid;" : "=r"(smid));
        asm volatile("mov.u32 %0, %%nsmid;" : "=r"(nsm));
        if (nsm == kGrid) bid = role_of_sm(smid);
    }
    if (threadIdx.x == kCW * 32 && bid < kStream) {
        const int m = bid % kSlots;
        const uint32_t sm0 = s2u(smem);
        asm volatile("cp.async.bulk.prefetch.L2.global [%0], %1;"
                     ::"l"(scal.p[bid & 3] + (bid >> 2) * (kNH * kS * 4 / kStream)), "n"(kNH * kS * 4 / kStream * 2) : "memory");
        for (int i = 0; i < 2 * kNS; i++) mbar_init(full0 + 8 * i, 1);
        asm volatile("fence.mbarrier_init.release.cluster;" ::: "memory");
        asm volatile("createpolicy.fractional.L2::evict_first.b64 %0, 1.0;" : "=l"(pol));
        const int* k0 = qk + (size_t)(bid / kSlots * kS + m * kHRows) * kD;
#pragma unroll
        for (int h = 0; h < 2; h++) {
            mbar_expect(full0 + 16 + 8 * h, kHalf);
            bulk_g2s_stream(sm0 + kChunk + h * kHalf, k0 + h * (kS / 2 * kD), kHalf, full0 + 16 + 8 * h, pol);
        }
#pragma unroll
        for (int h = 0; h < 2; h++) {
            mbar_expect(full0 + 8 * h, kHalf);
            bulk_g2s(sm0 + h * kHalf, kcos + (h * (kS / 2) + m * kHRows) * kD, kHalf / 2, full0 + 8 * h);
            bulk_g2s(sm0 + h * kHalf + kHalf / 2, ksin + (h * (kS / 2) + m * kHRows) * kD, kHalf / 2, full0 + 8 * h);
        }
#pragma unroll
        for (int h = 0; h < 2; h++) {
            mbar_expect(full0 + 32 + 8 * h, kHalf);
            bulk_g2s_stream(sm0 + 2 * kChunk + h * kHalf, k0 + (kTeams * kS + h * (kS / 2)) * kD, kHalf, full0 + 32 + 8 * h, pol);
        }
    }

    if (bid >= kStream) {
        const int team = bid - kStream;
        if (threadIdx.x == 0) s_misc[0] = ld_relaxed(&g_epoch);
        __syncthreads();
        if (threadIdx.x == 0 && atomicAdd(&g_arrive, 1u) == kGrid - 1) { g_arrive = 0u; g_epoch = s_misc[0] + 1u; }
        if (warp >= 3 * kMG) return;
        const int grp = warp / 3, t = threadIdx.x - grp * 96;
        constexpr int kRecBytes = kHeadWords * 8;
        if (t == 0) {
            mbar_init(s2u(smem + kOffBar) + grp * 8, 1);
            asm volatile("fence.mbarrier_init.release.cluster;" ::: "memory");
        }
        asm volatile("bar.sync %0, 96;" ::"r"(3 + grp) : "memory");
        for (int r = grp; r < kRounds; r += kMG) {
            const int g = r % kMG;
            const int tt = threadIdx.x - g * 96, qd = tt % 48, half = tt / 48;
            const uint32_t tag = round_tag(s_misc[0], r);
            const uint32_t tlo = tag & 15u, thi = tag >> 4;
            const unsigned long long* rec = g_rec + (size_t)(r % kPR * kTeams + team) * kHeadWords;
            unsigned long long ml, x[16], y[16];
            {
                const unsigned long long* buf = reinterpret_cast<const unsigned long long*>(smem + g * kRecBytes);
                const uint32_t mb = s2u(smem + kOffBar) + g * 8;
                if (tt < 32) {
                    const int want = r == kRounds - 1 ? kQuick : kSlots;
                    for (int i2 = 0;; i2++) {
                        ml = ld_rec1(rec + kSlots * kRecWords + lane);
                        if (__popc(__ballot_sync(0xffffffffu, ml_bad(ml, tag) == 0)) >= want) break;
                        if (i2 > kSpin) __trap();
                        __nanosleep(r >= kRounds - 2 ? kSleep : 5 * kSleep);
                    }
                    if (tt == 0) {
                        mbar_expect(mb, kRecBytes);
                        bulk_g2s(s2u(buf), rec, kRecBytes, mb);
                    }
                }
                mbar_wait(mb, (r / kMG) & 1);
                ml = buf[kSlots * kRecWords + lane];
#pragma unroll
                for (int i = 0; i < 16; i++) {
                    const ulonglong2 u = *reinterpret_cast<const ulonglong2*>(buf + (half * 16 + i) * kRecWords + 2 * qd);
                    x[i] = u.x; y[i] = u.y;
                }
                const unsigned long long* po = rec + half * 16 * kRecWords + 2 * qd;
                for (int it = 0;; it++) {
                    uint32_t any = ml_bad(ml, tag);
                    if (any) ml = ld_rec1(rec + kSlots * kRecWords + lane);
#pragma unroll
                    for (int i = 0; i < 16; i++) {
                        const uint32_t bad = rec_bad(x[i], tlo, thi) | rec_bad(y[i], tlo, thi);
                        if (bad) ld_rec2(po + i * kRecWords, x[i], y[i]);
                        any |= bad;
                    }
                    if (__all_sync(0xffffffffu, any == 0)) break;
                    if (it > kSpin) __trap();
                }
            }
            const float M = ml_m(ml);
            const float MM = warp_max(M);
            const float w = exp2f(M - MM);
            float LL = w * ml_l(ml);
#pragma unroll
            for (int o = 16; o > 0; o >>= 1) LL += __shfl_xor_sync(0xffffffffu, LL, o);
            float4 a = make_float4(0.f, 0.f, 0.f, 0.f);
#pragma unroll
            for (int i = 0; i < 16; i++) {
                const float wi = __shfl_sync(0xffffffffu, w, half * 16 + i);
                a.x = fmaf(wi, rec_lo(x[i]), a.x);
                a.y = fmaf(wi, rec_hi(x[i]), a.y);
                a.z = fmaf(wi, rec_lo(y[i]), a.z);
                a.w = fmaf(wi, rec_hi(y[i]), a.w);
            }
            float* rb = reinterpret_cast<float*>(smem + kMG * kRecBytes) + (2 * g + ((r / kMG) & 1)) * kD + 4 * qd;
            if (half == 1) *reinterpret_cast<float4*>(rb) = a;
            asm volatile("bar.sync %0, 96;" ::"r"(3 + g) : "memory");
            if (half == 0) {
                const float4 u = *reinterpret_cast<float4*>(rb);
                if ((unsigned)(r - kDef0) < (unsigned)kFHeads) {
                    unsigned long long* pre = g_pre + (size_t)(team * kFHeads + r - kDef0) * kPreWords;
                    const uint32_t ptag = s_misc[0] % 255u + 1u;
                    st_rec(pre + 2 * qd, a.x + u.x, a.y + u.y, ptag);
                    st_rec(pre + 2 * qd + 1, a.z + u.z, a.w + u.w, ptag);
                    if (qd == 0) st_ml(pre + 96, MM, LL, ptag);
                } else {
                    const float inv = __fdividef(1.0f, LL);
                    const __nv_bfloat162 o0 = __floats2bfloat162_rn((a.x + u.x) * inv, (a.y + u.y) * inv);
                    const __nv_bfloat162 o1 = __floats2bfloat162_rn((a.z + u.z) * inv, (a.w + u.w) * inv);
                    uint2 ov;
                    ov.x = *reinterpret_cast<const uint32_t*>(&o0);
                    ov.y = *reinterpret_cast<const uint32_t*>(&o1);
                    *reinterpret_cast<uint2*>(out + (size_t)(kTeams * r + team) * kD + 4 * qd) = ov;
                }
            }
            if (tt == 95)
                asm volatile("st.relaxed.gpu.global.u32 [%0], %1;" ::"l"(&g_mdone[(team * kMG + g) * 32]), "r"(s_misc[0] * kRounds + r + 1) : "memory");
        }
        return;
    }

    const int m = bid % kSlots, team = bid / kSlots;
    const int row0 = m * kHRows;

    if (warp == kCW) {
        const size_t off0 = ((size_t)team * kS + row0) * kD;
        const uint32_t sm0 = s2u(smem);
        if (lane == 0) {
            const unsigned int epoch = ld_relaxed(&g_epoch);
            s_misc[0] = epoch;
            s_misc[1] = 0;
            for (int j = 0; j < kNP; j++) {
                s_misc[4 + 2 * j] = epoch * (kStream * (4 * kRounds - 2));
                s_misc[5 + 2 * j] = clock32();
            }
        }
        __syncwarp();
        asm volatile("bar.sync 2, %0;" ::"n"(kThreads) : "memory");
        if (lane < kFBoxes) {
            constexpr unsigned kMask = (1u << kFBoxes) - 1;
            const int h = lane / (kFBoxes / 2);
            const bool first = lane % (kFBoxes / 2) == 0;
            asm volatile("createpolicy.fractional.L2::evict_first.b64 %0, 1.0;" : "=l"(pol));
            const unsigned int base = s_misc[0] * (kStream * (4 * kRounds - 2));
            const int phase = (2 * team - (kTeams - 1)) * (kStream / 2) + (m - kSlots / 2) * kWaveSlot + (h ? -kWaveHalf : kWaveHalf);
            int u = kNS;
            const int* kp = qk + off0 + h * (kS / 2 * kD);
            const int* vp = qv + off0 + h * (kS / 2 * kD);
            for (int p = 2; p < 2 * kRounds + kF; p++) {
                const int pos = 2 * p + h;
                const bool fin = p >= 2 * kRounds;
                const bool isv = (p & 1) == 0 || p == 2 * kRounds - 1;
                const int r = p == 2 * kRounds - 1 ? kRounds - 1 : isv ? (p >> 1) - 1 : (p + 1) >> 1;
                const int ramp = max(min(min(pos - 4, 4 * kRounds - pos), kWaveRamp), 0);
                const int inblk = (3 * (((r * kTeams + team) * 2 + h) * kSlots + m) + 1 + kBlock8 - (isv ? kOriginV : kOriginK)) % kBlock8;
                const int tau = kStream * pos + (phase + (isv ? kWaveV : -kWaveV) + (kBlock8 / 2 - inblk) * kBurst / 12) * ramp / kWaveRamp;
                const int gone = min(max(tau - kStream * (4 * kDef0 + 3), 0), 4 * kStream * kFHeads) * kF / (2 * kFHeads);
                const unsigned int need = base + tau - gone - max(kRampEnd - pos, 0) * kRampStep -
                                          (fin ? kLeadEnd - lane % (kFBoxes / 2) * kBoxStep : kLead);
                const bool skip = isv && deferred_to(4 * h + m / 8, r) < kF;
                const int slot = u >= kNS ? u - kNS : u;
                const uint32_t dst = sm0 + slot * kChunk + lane * (kChunk / kFBoxes), fullb = full0 + 16 * slot + 8 * h;
                const int* src = (isv ? vp : kp) + (size_t)r * (kTeams * kS * kD);
                const int row = (kTeams * (kDef0 + m / kFG) + team) * kS + ((kF * (m / kFG) + p - 2 * kRounds) & (kFHeads - 1)) * kFRows +
                                lane * (kFRows / kFBoxes);
                const uint32_t fb = fine + 8 * (kFBoxes * (p - 2 * kRounds) + lane);
                bool todo = !skip && (first || fin);
                const uint32_t par = u >= kNS ? 0 : 1;
                if (!skip) u = u + 1 == 2 * kNS ? 0 : u + 1;
                bool free = false;
                for (int it = 0; __any_sync(kMask, todo); it++) {
                    uint32_t x, tx, y, ty;
                    asm volatile("ld.volatile.shared.v4.u32 {%0, %1, %2, %3}, [%4];"
                                 : "=r"(x), "=r"(tx), "=r"(y), "=r"(ty) : "r"(sm0 + kOffMisc + 16) : "memory");
                    if (todo && !free) {
                        uint32_t ok;
                        asm volatile("{\n.reg .pred p;\nmbarrier.test_wait.parity.shared::cta.b64 p, [%1], %2;\nselp.u32 %0, 1, 0, p;\n}"
                                     : "=r"(ok) : "r"(fullb + 2 * kNS * 8), "r"(par) : "memory");
                        free = ok;
                        if (free && !fin) mbar_expect(fullb, kHalf);
                    }
                    const uint32_t now = clock32();
                    x += min(((now - tx) * kRate) >> 10, kAhead);
                    y += min(((now - ty) * kRate) >> 10, kAhead);
                    const bool go = todo && free && (int)((x - need) & (y - need)) >= 0;
                    if (it > 16 * kSpin) __trap();
                    if (!__any_sync(kMask, go)) continue;
                    asm volatile("{\n.reg .pred p, q;\nsetp.ne.u32 p, %9, 0;\nsetp.ne.u32 q, %10, 0;\n"
                                 "@p cp.async.bulk.shared::cluster.global.mbarrier::complete_tx::bytes.L2::cache_hint [%0], [%1], %2, [%3], %4;\n"
                                 "@q cp.async.bulk.tensor.2d.shared::cluster.global.tile.mbarrier::complete_tx::bytes.L2::cache_hint [%0], [%5, {%6, %7}], [%8], %4;\n}"
                                 ::"r"(dst), "l"(src), "n"(kHalf), "r"(fullb), "l"(pol), "l"(&tmv), "r"((m % kFG) * kFW), "r"(row), "r"(fb),
                                   "r"((uint32_t)(go && !fin)), "r"((uint32_t)(go && fin)) : "memory");
                    todo = todo && !go;
                }
            }
            if (lane == 0) s_misc[1] = 1;
        }
    } else if (warp >= kCW + 2) {
        asm volatile("bar.sync 2, %0;" ::"n"(kThreads) : "memory");
        if (lane == 0) {
            const int j = warp - (kCW + 2);
            for (int it = 0; !s_misc[1]; it++) {
                const uint32_t t = clock32();
                const uint32_t v = ld_relaxed(prog_counter(j));
                asm volatile("st.volatile.shared.v2.u32 [%0], {%1, %2};" ::"r"(s2u(smem) + kOffMisc + 16 + 8 * j), "r"(v), "r"(t) : "memory");
                if (s_misc[1]) break;
                if (it > kSpin) __trap();
                __nanosleep(kPollSleep);
            }
        }
    } else if (warp == kCW + 1) {
        {
            if (lane < 2 * kNS + 6) mbar_init(empty0 + 8 * lane, lane < 2 * kNS ? kCW / 2 : (lane >= 2 * kNS + 2 && lane < 2 * kNS + 4) ? 1 : kCW);
            asm volatile("fence.mbarrier_init.release.cluster;" ::: "memory");
        }
        asm volatile("bar.sync 2, %0;" ::"n"(kThreads) : "memory");
        const unsigned int epoch = s_misc[0];
        if (lane == 0 && atomicAdd(&g_arrive, 1u) == kGrid - 1) { g_arrive = 0u; g_epoch = epoch + 1u; }
        {
            const uint32_t sm0 = s2u(smem);
            const __nv_bfloat16* src = scal.p[lane >> 3] + (size_t)team * kS + row0 + (lane & 4) * (kS / 8) + (lane & 3) * 8;
            const __nv_bfloat16* qs = q + team * kD + lane * 8;
#pragma unroll 1
            for (int r = kEarly; r < kRounds; r++) {
                cp16(sm0 + kOffScal + r * 512 + lane * 16, src + (size_t)r * (kTeams * kS));
                if (lane < 24) cp16(sm0 + kOffQ + r * (kD * 2) + lane * 16, qs + r * (kTeams * kD));
                if (r == 2 * kEarly - 1 || r == kRounds - 1) asm volatile("cp.async.commit_group;" ::: "memory");
            }
        }
        uint32_t cs[2][4];
#pragma unroll
        for (int i = 0; i < 2; i++) {
            const int p = (lane + 32 * i) % 48;
            cs[i][0] = ld_pair(qcos + 2 * p); cs[i][1] = ld_pair(qcos + 2 * p + 96);
            cs[i][2] = ld_pair(qsin + 2 * p); cs[i][3] = ld_pair(qsin + 2 * p + 96);
        }
        asm volatile("cp.async.wait_group 1;" ::: "memory");
        __syncwarp();
        for (int r = 0; r < kRounds; r++) {
            const float* sc = reinterpret_cast<const float*>(smem + kOffSc) + (r & 1) * (kCW * kScStride);
            const uint32_t tag = round_tag(epoch, r);
            unsigned long long* rec = g_rec + (size_t)(r % kPR * kTeams + team) * kHeadWords;
            if (r >= kEarly && r < kEarly + kF * kFBoxes && lane == 0) {
                mbar_init(fine + 8 * (r - kEarly), 1);
                asm volatile("fence.mbarrier_init.release.cluster;" ::: "memory");
                mbar_expect(fine + 8 * (r - kEarly), kChunk / kFBoxes);
                asm volatile("fence.proxy.async.shared::cta;" ::: "memory");
            }
            if (r == kPrep + m / 2) {
                const unsigned long long* pre = g_pre + (size_t)(team * kFHeads + m / kFG) * kPreWords;
                const unsigned long long* lgp = g_lg + (size_t)(team * kFHeads + m / kFG) * (kF * kFRows);
                const uint32_t ptag = epoch % 255u + 1u;
                unsigned long long ml, po;
                for (int it = 0;; it++) {
                    ml = ld_rec1(pre + 96);
                    po = ld_rec1(pre + (m % kFG) * (kFW / 2) + lane % (kFW / 2));
                    if (!(ml_bad(ml, ptag) | rec_bad(po, ptag & 15u, ptag >> 4))) break;
                    if (it > kSpin) __trap();
                }
                const float inv = 1.0f / ml_l(ml);
                if (lane < kFW / 2) {
                    reinterpret_cast<float2*>(smem + kOffFin)[lane] = make_float2(rec_lo(po) * inv, rec_hi(po) * inv);
                }
#pragma unroll 1
                for (int c = 0; c < kF; c++) {
                    unsigned long long u[8];
                    for (int it = 0;; it++) {
                        uint32_t bad = 0;
#pragma unroll
                        for (int k = 0; k < 8; k++) {
                            u[k] = ld_rec1(lgp + c * kFRows + 32 * k + lane);
                            bad |= ml_bad(u[k], ptag);
                        }
                        if (!bad) break;
                        if (it > kSpin) __trap();
                    }
#pragma unroll
                    for (int k = 0; k < 8; k++)
                        reinterpret_cast<float*>(smem + kOffW)[c * kFRows + 32 * k + lane] = ml_l(u[k]) * exp2f(ml_m(u[k]) - ml_m(ml)) * inv;
                }
                __syncwarp();
            }
            if (r == kRounds - 3 && lane == 0) asm volatile("prefetch.tensormap [%0];" ::"l"(&tmv) : "memory");
            if (r == kEarly) {
                asm volatile("cp.async.wait_all;" ::: "memory");
                __syncwarp();
            }
            if (r + kEarly < kRounds) {
                uint32_t* qrow = reinterpret_cast<uint32_t*>(smem + kOffQ + (r + kEarly) * (kD * 2));
                rotate_q(qrow, lane, cs[0][0], cs[0][1], cs[0][2], cs[0][3]);
                if (lane < 16) rotate_q(qrow, lane + 32, cs[1][0], cs[1][1], cs[1][2], cs[1][3]);
            }
            if (r >= kPR) {
                const unsigned int* mdone = &g_mdone[(team * kMG + r % kMG) * 32];
                const unsigned int need = epoch * kRounds + r - kPR + 1;
                for (int it = 0; (int)(ld_relaxed(mdone) - need) < 0; it++)
                    if (it > kSpin) __trap();
            }
            mbar_wait(sfull + 8 * (r & 1), (r >> 1) & 1);
            const float M = sc[0];
            float L = lane < kCW ? sc[lane * kScStride + 1] : 0.f;
            float acc[2][6];
#pragma unroll
            for (int ww = 0; ww < kCW; ww++) {
#pragma unroll
                for (int j = 0; j < 3; j++) {
                    const float2 t = *reinterpret_cast<const float2*>(sc + ww * kScStride + 4 + 64 * j + 2 * lane);
                    acc[ww & 1][2 * j] = ww < 2 ? t.x : acc[ww & 1][2 * j] + t.x;
                    acc[ww & 1][2 * j + 1] = ww < 2 ? t.y : acc[ww & 1][2 * j + 1] + t.y;
                }
                if ((ww & 3) == 3 && ww < 15) L += __shfl_xor_sync(0xffffffffu, L, 8 >> (ww >> 2));
            }
            L += __shfl_xor_sync(0xffffffffu, L, 1);
#pragma unroll
            for (int j = 0; j < 3; j++)
                st_rec(rec + m * kRecWords + 32 * j + lane, acc[0][2 * j] + acc[1][2 * j], acc[0][2 * j + 1] + acc[1][2 * j + 1], tag);
            if (lane == 0) st_ml(rec + kSlots * kRecWords + m, M, L, tag);
            __syncwarp();
            if (lane == 0) mbar_arrive(sempty + 8 * (r & 1));
        }
    } else {
        int dp[3];
#pragma unroll
        for (int j = 0; j < 3; j++) dp[j] = (64 * j + 2 * lane + 96) % kD;
        {
            const uint32_t sm0 = s2u(smem);
            if (warp < kEarly) {
                cp16(sm0 + kOffScal + threadIdx.x * 16, scal.p[lane >> 3] + (size_t)(kTeams * warp + team) * kS + row0 + (lane & 4) * (kS / 8) + (lane & 3) * 8);
            } else if (warp < 2 * kEarly && lane < 24) {
                cp16(sm0 + kOffQ + (warp - kEarly) * (kD * 2) + lane * 16, q + (size_t)(kTeams * (warp - kEarly) + team) * kD + lane * 8);
            }
            asm volatile("cp.async.commit_group;" ::: "memory");
        }
        const int p = threadIdx.x % 48, g = threadIdx.x / 48;
        const uint32_t c_lo = ld_pair(qcos + 2 * p), c_hi = ld_pair(qcos + 2 * p + 96);
        const uint32_t s_lo = ld_pair(qsin + 2 * p), s_hi = ld_pair(qsin + 2 * p + 96);
        float kc[kR][6], ks[kR][6];
        asm volatile("bar.sync 2, %0;" ::"n"(kThreads) : "memory");
        unsigned int* prog = prog_counter(((m >> 1) ^ (m >> 4) ^ team) & 1);
        const int mute = (m & 1) * 256;
        const int half = warp / (kCW / 2);
        const uint32_t fullh = full0 + 8 * half, emptyh = empty0 + 8 * half;
        mbar_wait(fullh, 0);
#pragma unroll
        for (int i = 0; i < kR; i++) {
            const unsigned char* cb = smem + half * (kHalf / 2) + (warp * kR + i) * (kD * 2);
#pragma unroll
            for (int j = 0; j < 3; j++) {
                const uint32_t uc = *reinterpret_cast<const uint32_t*>(cb + 128 * j + 4 * lane);
                const uint32_t us = *reinterpret_cast<const uint32_t*>(cb + kHalf / 2 + 2 * dp[j]);
                kc[i][2 * j] = bf_lo(uc); kc[i][2 * j + 1] = bf_hi(uc);
                const float sg = (j == 0 || (j == 1 && lane < 16)) ? 1.f : -1.f;
                ks[i][2 * j] = sg * bf_lo(us); ks[i][2 * j + 1] = sg * bf_hi(us);
            }
        }
        __syncwarp();
        if (lane == 0) mbar_arrive(emptyh);
        asm volatile("cp.async.wait_group 0;" ::: "memory");
        asm volatile("bar.sync 1, %0;" ::"n"(kCW * 32) : "memory");
        if (g < kEarly) rotate_q(reinterpret_cast<uint32_t*>(smem + kOffQ + g * (kD * 2)), p, c_lo, c_hi, s_lo, s_hi);
        asm volatile("bar.sync 1, %0;" ::"n"(kCW * 32) : "memory");
        const float scale_log2e = 1.4426950408889634f * rsqrtf((float)kD);
        float* my0 = reinterpret_cast<float*>(smem + kOffSc) + warp * kScStride;

        float* s_max = reinterpret_cast<float*>(smem + kOffMax);
        int slot = 1;
        uint32_t ph = 0;
        float lgc[kR] = {0.f, 0.f, 0.f, 0.f};
        for (int it = 0; it <= kRounds; it++) {
            float lg[kR];
            if (it < kRounds) {
                float qa[6], qb[6];
#pragma unroll
                for (int j = 0; j < 3; j++) {
                    const uint32_t qo = *reinterpret_cast<const uint32_t*>(smem + kOffQ + it * (kD * 2) + 2 * (64 * j + 2 * lane));
                    const uint32_t qp = *reinterpret_cast<const uint32_t*>(smem + kOffQ + it * (kD * 2) + 2 * dp[j]);
                    qa[2 * j] = bf_lo(qo); qa[2 * j + 1] = bf_hi(qo);
                    qb[2 * j] = bf_lo(qp); qb[2 * j + 1] = bf_hi(qp);
                }
                const unsigned char* sp = smem + kOffScal + it * (4 * kRows * 2) + warp * (kR * 2);
                const uint2 uks = *reinterpret_cast<const uint2*>(sp);
                const uint2 ukz = *reinterpret_cast<const uint2*>(sp + kRows * 2);
                const float kz[4] = {bf_lo(ukz.x), bf_hi(ukz.x), bf_lo(ukz.y), bf_hi(ukz.y)};
                const float sk[4] = {bf_lo(uks.x), bf_hi(uks.x), bf_lo(uks.y), bf_hi(uks.y)};
                mbar_wait(fullh + 16 * slot, ph);
                if ((threadIdx.x & 255) == mute) asm volatile("red.relaxed.gpu.global.add.u32 [%0], %1;" ::"l"(prog), "n"(kSample) : "memory");
                const unsigned char* kb = smem + slot * kChunk + warp * (kR * kRowBytes) + lane * 8;
#pragma unroll
                for (int i = 0; i < kR; i++) {
                    float dot = 0.f;
#pragma unroll
                    for (int j = 0; j < 3; j++) {
                        const int2 kk = *reinterpret_cast<const int2*>(kb + i * kRowBytes + 256 * j);
                        const float e0 = qa[2 * j] * kc[i][2 * j] + qb[2 * j] * ks[i][2 * j];
                        const float e1 = qa[2 * j + 1] * kc[i][2 * j + 1] + qb[2 * j + 1] * ks[i][2 * j + 1];
                        dot = fmaf((float)kk.x - kz[i], e0, dot);
                        dot = fmaf((float)kk.y - kz[i], e1, dot);
                    }
                    lg[i] = dot;
                }
                __syncwarp();
                if (lane == 0) mbar_arrive(emptyh + 16 * slot);
                if (++slot == kNS) { slot = 0; ph ^= 1; }
#pragma unroll
                for (int o = 16; o > 0; o >>= 1) {
#pragma unroll
                    for (int i = 0; i < kR; i++) lg[i] += __shfl_xor_sync(0xffffffffu, lg[i], o);
                }
                float mw = -INFINITY;
#pragma unroll
                for (int i = 0; i < kR; i++) {
                    lg[i] = lg[i] * sk[i] * scale_log2e;
                    mw = fmaxf(mw, lg[i]);
                }
                if (lane == 0) {
                    s_max[(it & 3) * kCW + warp] = mw;
                    mbar_arrive(mxbar + 8 * (it & 1));
                }
            }
            if (it > 0) {
                const int r = it - 1;
                float* my = my0 + (r & 1) * (kCW * kScStride);
                const int df = deferred_to(4 * half + m / 8, r);
                const unsigned char* sp = smem + kOffScal + r * (4 * kRows * 2) + warp * (kR * 2);
                const uint2 uvs = *reinterpret_cast<const uint2*>(sp + 2 * kRows * 2);
                const uint2 uvz = *reinterpret_cast<const uint2*>(sp + 3 * kRows * 2);
                const float vz[4] = {bf_lo(uvz.x), bf_hi(uvz.x), bf_lo(uvz.y), bf_hi(uvz.y)};
                const float sv[4] = {bf_lo(uvs.x), bf_hi(uvs.x), bf_lo(uvs.y), bf_hi(uvs.y)};
                mbar_wait(mxbar + 8 * (r & 1), (r >> 1) & 1);
                float M;
                {
                    const float4* pm4 = reinterpret_cast<const float4*>(s_max + (r & 3) * kCW);
                    const float4 m0 = pm4[0], m1 = pm4[1], m2 = pm4[2], m3 = pm4[3];
                    M = fmaxf(fmaxf(fmaxf(fmaxf(m0.x, m0.y), fmaxf(m0.z, m0.w)), fmaxf(fmaxf(m1.x, m1.y), fmaxf(m1.z, m1.w))),
                              fmaxf(fmaxf(fmaxf(m2.x, m2.y), fmaxf(m2.z, m2.w)), fmaxf(fmaxf(m3.x, m3.y), fmaxf(m3.z, m3.w))));
                }
                float lw = 0.f, cz = 0.f, pv[kR];
#pragma unroll
                for (int i = 0; i < kR; i++) {
                    const float p = exp2f(lgc[i] - M);
                    lw += p;
                    pv[i] = p * sv[i];
                    cz = fmaf(pv[i], vz[i], cz);
                }
                mbar_wait(sempty + 8 * (r & 1), ((r >> 1) & 1) ^ 1);
                if (lane == 0) { my[0] = M; my[1] = lw; }
                float acc[6] = {-cz, -cz, -cz, -cz, -cz, -cz};
                if (df < kF) {
                    if (lane < kR)
                        st_ml(g_lg + ((team * kFHeads + r - kDef0) * kF + df) * kFRows + (m % 8) * kHRows + (warp % 8) * kR + lane, M,
                              lane == 0 ? pv[0] : lane == 1 ? pv[1] : lane == 2 ? pv[2] : pv[3], s_misc[0] % 255u + 1u);
                } else {
                    mbar_wait(fullh + 16 * slot, ph);
                    if ((threadIdx.x & 255) == mute) asm volatile("red.relaxed.gpu.global.add.u32 [%0], %1;" ::"l"(prog), "n"(kSample) : "memory");
                    const unsigned char* vb = smem + slot * kChunk + warp * (kR * kRowBytes) + lane * 8;
#pragma unroll
                    for (int i = 0; i < kR; i++) {
#pragma unroll
                        for (int j = 0; j < 3; j++) {
                            const int2 vv = *reinterpret_cast<const int2*>(vb + i * kRowBytes + 256 * j);
                            acc[2 * j] = fmaf(pv[i], (float)vv.x, acc[2 * j]);
                            acc[2 * j + 1] = fmaf(pv[i], (float)vv.y, acc[2 * j + 1]);
                        }
                    }
                    __syncwarp();
                    if (lane == 0) mbar_arrive(emptyh + 16 * slot);
                    if (++slot == kNS) { slot = 0; ph ^= 1; }
                }
#pragma unroll
                for (int j = 0; j < 3; j++)
                    *reinterpret_cast<float2*>(my + 4 + 64 * j + 2 * lane) = make_float2(acc[2 * j], acc[2 * j + 1]);
                __syncwarp();
                if (lane == 0) mbar_arrive(sfull + 8 * (r & 1));
            }
#pragma unroll
            for (int i = 0; i < kR; i++) lgc[i] = lg[i];
        }
        {
            const int cp = lane < kFW / 2 ? lane : 0;
            const int ft = threadIdx.x < kFW ? threadIdx.x : 0;
            const float fin = reinterpret_cast<const float*>(smem + kOffFin)[ft];
            __nv_bfloat16* op = out + (size_t)(kTeams * (kDef0 + m / kFG) + team) * kD + (m % kFG) * kFW + ft;
            float a0 = 0.f, a1 = 0.f, b0 = 0.f, b1 = 0.f;
#pragma unroll 1
            for (int f = 0; f < kF; f++) {
                const float* sw = reinterpret_cast<const float*>(smem + kOffW) + f * kFRows + (warp >> 2) * 16 + (warp & 3) * 4;
                const unsigned char* vb = smem + slot * kChunk + ((warp >> 2) * 16 + (warp & 3) * 4) * (kFW * 4) + cp * 8;
                const uint32_t fb = fine + (f * kFBoxes + (warp >> 2)) * 8;
                float* part = reinterpret_cast<float*>(smem + kOffPart) + f * kPartSize;
                float4 w[4];
#pragma unroll
                for (int k = 0; k < 4; k++) w[k] = *reinterpret_cast<const float4*>(sw + 64 * k);
#pragma unroll
                for (int k = 0; k < 4; k++) {
                    mbar_wait(fb + 32 * k, 0);
                    if ((k & 1) && threadIdx.x == kCW * 32 - 32 + mute && f < kF - 1) asm volatile("red.relaxed.gpu.global.add.u32 [%0], %1;" ::"l"(prog), "n"(kSample) : "memory");
                    const int2 v0 = *reinterpret_cast<const int2*>(vb + k * (64 * kFW * 4));
                    const int2 v1 = *reinterpret_cast<const int2*>(vb + k * (64 * kFW * 4) + kFW * 4);
                    const int2 v2 = *reinterpret_cast<const int2*>(vb + k * (64 * kFW * 4) + 2 * kFW * 4);
                    const int2 v3 = *reinterpret_cast<const int2*>(vb + k * (64 * kFW * 4) + 3 * kFW * 4);
                    a0 = fmaf(w[k].x, (float)v0.x, a0); a1 = fmaf(w[k].x, (float)v0.y, a1);
                    b0 = fmaf(w[k].y, (float)v1.x, b0); b1 = fmaf(w[k].y, (float)v1.y, b1);
                    a0 = fmaf(w[k].z, (float)v2.x, a0); a1 = fmaf(w[k].z, (float)v2.y, a1);
                    b0 = fmaf(w[k].w, (float)v3.x, b0); b1 = fmaf(w[k].w, (float)v3.y, b1);
                }
                if (lane < kFW / 2) {
                    part[lane * kPartStride + warp] = a0 + b0;
                    part[kPartOdd + lane * kPartStride + warp] = a1 + b1;
                }
                if (warp >= 2) {
                    asm volatile("bar.arrive %0, %1;" ::"r"(3 + f), "n"(kCW * 32) : "memory");
                } else {
                    asm volatile("bar.sync %0, %1;" ::"r"(3 + f), "n"(kCW * 32) : "memory");
                    const float4* ps = reinterpret_cast<const float4*>(part + (ft & 1) * kPartOdd + (ft >> 1) * kPartStride);
                    const float4 p0 = ps[0], p1 = ps[1], p2 = ps[2], p3 = ps[3];
                    const float sum = (((p0.x + p0.y) + (p0.z + p0.w)) + ((p1.x + p1.y) + (p1.z + p1.w))) +
                                      (((p2.x + p2.y) + (p2.z + p2.w)) + ((p3.x + p3.y) + ((p3.z + p3.w) + fin)));
                    asm volatile("{\n.reg .pred p;\n.reg .b16 h;\nsetp.ne.u32 p, %2, 0;\ncvt.rn.bf16.f32 h, %1;\n@p st.global.b16 [%0], h;\n}"
                                 ::"l"(op), "f"(sum), "r"((uint32_t)(f == kF - 1 && threadIdx.x < kFW)) : "memory");
                }
                if (++slot == kNS) slot = 0;
            }
        }
    }
}

__global__ void __launch_bounds__(256)
attn_fallback(const __nv_bfloat16* __restrict__ q, const int* __restrict__ qk,
              const __nv_bfloat16* __restrict__ ksc, const __nv_bfloat16* __restrict__ kzp,
              const int* __restrict__ qv, const __nv_bfloat16* __restrict__ vsc,
              const __nv_bfloat16* __restrict__ vzp, const __nv_bfloat16* __restrict__ qcos,
              const __nv_bfloat16* __restrict__ qsin, const __nv_bfloat16* __restrict__ kcos,
              const __nv_bfloat16* __restrict__ ksin, __nv_bfloat16* __restrict__ out) {
    __shared__ float qr[kD], lg[kS], red[8];
    const int h = blockIdx.x, t = threadIdx.x, warp = t >> 5, lane = t & 31;
    if (t < kD) {
        const float x = __bfloat162float(q[h * kD + t]);
        const float y = t < kD / 2 ? -__bfloat162float(q[h * kD + t + kD / 2]) : __bfloat162float(q[h * kD + t - kD / 2]);
        qr[t] = bf_round(bf_round(x * __bfloat162float(qcos[t])) + bf_round(y * __bfloat162float(qsin[t])));
    }
    __syncthreads();
    const float scale_log2e = 1.4426950408889634f * rsqrtf((float)kD);
    float mw = -INFINITY;
    for (int s = warp; s < kS; s += 8) {
        const size_t row = (size_t)h * kS + s;
        const float z = __bfloat162float(kzp[row]);
        float dot = 0.f;
        for (int d = lane; d < kD; d += 32) {
            const int dp = d < kD / 2 ? d + kD / 2 : d - kD / 2;
            const float sn = __bfloat162float(ksin[s * kD + dp]);
            const float e = qr[d] * __bfloat162float(kcos[s * kD + d]) + qr[dp] * (d < kD / 2 ? sn : -sn);
            dot = fmaf((float)qk[row * kD + d] - z, e, dot);
        }
        for (int o = 16; o > 0; o >>= 1) dot += __shfl_xor_sync(0xffffffffu, dot, o);
        dot = dot * __bfloat162float(ksc[row]) * scale_log2e;
        if (lane == 0) lg[s] = dot;
        mw = fmaxf(mw, dot);
    }
    if (lane == 0) red[warp] = mw;
    __syncthreads();
    float M = red[0];
    for (int i = 1; i < 8; i++) M = fmaxf(M, red[i]);
    __syncthreads();
    float l = 0.f;
    for (int s = t; s < kS; s += 256) { const float p = exp2f(lg[s] - M); l += p; lg[s] = p; }
    for (int o = 16; o > 0; o >>= 1) l += __shfl_xor_sync(0xffffffffu, l, o);
    if (lane == 0) red[warp] = l;
    __syncthreads();
    float L = 0.f;
    for (int i = 0; i < 8; i++) L += red[i];
    if (t < kD) {
        float acc = 0.f;
        for (int s = 0; s < kS; s++) {
            const size_t row = (size_t)h * kS + s;
            acc = fmaf(lg[s] * __bfloat162float(vsc[row]), (float)qv[row * kD + t] - __bfloat162float(vzp[row]), acc);
        }
        out[h * kD + t] = __float2bfloat16_rn(acc / L);
    }
}

}

extern "C" void kernel_launch(void* const* d_in, const int* in_sizes, int n_in, void* d_out, int out_size) {
    const __nv_bfloat16* q = (const __nv_bfloat16*)d_in[0];
    const int* qk = (const int*)d_in[1];
    const __nv_bfloat16* ksc = (const __nv_bfloat16*)d_in[2];
    const __nv_bfloat16* kzp = (const __nv_bfloat16*)d_in[3];
    const int* qv = (const int*)d_in[4];
    const __nv_bfloat16* vsc = (const __nv_bfloat16*)d_in[5];
    const __nv_bfloat16* vzp = (const __nv_bfloat16*)d_in[6];
    const __nv_bfloat16* qcos = (const __nv_bfloat16*)d_in[7];
    const __nv_bfloat16* qsin = (const __nv_bfloat16*)d_in[8];
    const __nv_bfloat16* kcos = (const __nv_bfloat16*)d_in[9];
    const __nv_bfloat16* ksin = (const __nv_bfloat16*)d_in[10];

    typedef CUresult (*EncodeFn)(CUtensorMap*, CUtensorMapDataType, cuuint32_t, void*, const cuuint64_t*, const cuuint64_t*,
                                 const cuuint32_t*, const cuuint32_t*, CUtensorMapInterleave, CUtensorMapSwizzle,
                                 CUtensorMapL2promotion, CUtensorMapFloatOOBfill);
    static EncodeFn encode = nullptr;
    static int by_sm = 0;
    static int mode = 0;
    if (!mode) {
        int dev = 0, sms = 0, occ = 0;
        cudaGetDevice(&dev);
        cudaDeviceGetAttribute(&sms, cudaDevAttrMultiProcessorCount, dev);
        cudaError_t e = cudaFuncSetAttribute(attn_kernel, cudaFuncAttributeMaxDynamicSharedMemorySize, kSmemBytes);
        if (e == cudaSuccess) e = cudaOccupancyMaxActiveBlocksPerMultiprocessor(&occ, attn_kernel, kThreads, kSmemBytes);
        void* fn = nullptr;
        cudaDriverEntryPointQueryResult qr;
        if (e == cudaSuccess) e = cudaGetDriverEntryPoint("cuTensorMapEncodeTiled", &fn, cudaEnableDefault, &qr);
        encode = (EncodeFn)fn;
        mode = (e == cudaSuccess && fn && occ * sms >= kGrid) ? 1 : 2;
        (void)cudaGetLastError();
        by_sm = sms == kGrid && occ == 1;
    }
    CUtensorMap tmv;
    bool fast = mode == 1;
    if (fast) {
        const cuuint64_t dims[2] = {(cuuint64_t)kD, (cuuint64_t)kNH * kS}, strides[1] = {(cuuint64_t)kRowBytes};
        const cuuint32_t box[2] = {(cuuint32_t)kFW, (cuuint32_t)(kFRows / kFBoxes)}, es[2] = {1, 1};
        fast = encode(&tmv, CU_TENSOR_MAP_DATA_TYPE_INT32, 2, (void*)qv, dims, strides, box, es, CU_TENSOR_MAP_INTERLEAVE_NONE,
                      CU_TENSOR_MAP_SWIZZLE_NONE, CU_TENSOR_MAP_L2_PROMOTION_L2_128B, CU_TENSOR_MAP_FLOAT_OOB_FILL_NONE) == CUDA_SUCCESS;
    }
    if (fast)
        attn_kernel<<<kGrid, kThreads, kSmemBytes>>>(Scalars{{ksc, kzp, vsc, vzp}}, qk, by_sm, kcos, ksin, qv, q, qcos, qsin,
                                                     (__nv_bfloat16*)d_out, tmv);
    else
        attn_fallback<<<kNH, 256>>>(q, qk, ksc, kzp, qv, vsc, vzp, qcos, qsin, kcos, ksin, (__nv_bfloat16*)d_out);
}
```

```cpp
#include <cuda_runtime.h>
#include <cuda.h>
#include <cuda_bf16.h>
#include <stdint.h>

namespace {

constexpr int kB = 8, kH = 32, kS = 2048, kD = 192;
constexpr int kNH = kB * kH;
constexpr int kTeams = 4;
constexpr int kSlots = 32;
constexpr int kRows = kS / kSlots;
constexpr int kRounds = kNH / kTeams;
constexpr int kStream = kTeams * kSlots;
constexpr int kGrid = kStream + kTeams;
constexpr int kCW = 16;
constexpr int kR = kRows / kCW;
constexpr int kThreads = (kCW + 4) * 32;
constexpr int kRowBytes = kD * 4;
constexpr int kChunk = kRows * kRowBytes;
constexpr int kNS = 3;
constexpr int kHalf = kChunk / 2;
constexpr int kHRows = kRows / 2;
constexpr int kLead = 200;
constexpr int kLeadEnd = 215, kBoxStep = 12;
constexpr int kRampEnd = 12, kRampStep = 70;
constexpr int kWaveSlot = 4, kWaveRamp = 4;
constexpr int kBlock8 = 160;
constexpr int kOriginK = 1 * 32, kOriginV = 4 * 32;
constexpr int kTurn3 = kBlock8;
constexpr int kLagV3 = (3 * 6 * kStream + 4 * (kOriginV - kOriginK + kBlock8)) % (4 * kTurn3);
constexpr int kTurnV = kLagV3 < 3 * kTurn3 / 2 ? 1 : kLagV3 < 5 * kTurn3 / 2 ? 2 : 3;
constexpr int kWaveV = (kTurnV * kTurn3 - kLagV3) / 6;
constexpr int kWaveG = ((kTurnV == 2 ? 1 : 2) * kTurn3 - 4 * (kBlock8 - 3 * (kNH / 2) * 2 * kSlots % kBlock8)) / 6;
constexpr uint32_t kRate = 69, kAhead = 256;
constexpr int kSample = 4;
constexpr int kSmooth = 3, kJump = 80;
constexpr int kPollSleep = 100;
constexpr int kQuick = 20;
constexpr int kSleep = 200;
constexpr int kPR = 12;
constexpr int kScStride = 196;
constexpr int kOffScal = kNS * kChunk;
constexpr int kOffQ = kOffScal + kRounds * 4 * kRows * 2;
constexpr int kOffSc = kOffQ + kRounds * kD * 2;
constexpr int kOffBar = kOffSc + 2 * kCW * kScStride * 4;
constexpr int kF = 3;
constexpr int kFG = 4;
constexpr int kFW = kD / kFG;
constexpr int kFRows = kRows * kFG;
constexpr int kFHeads = kSlots / kFG;
constexpr int kDef0 = 18;
constexpr int kEarly = 4;
constexpr int kFBoxes = 16;
constexpr int kPrep = 40;
constexpr int kOffW = kOffScal;
constexpr int kOffFin = kOffW + kF * kFRows * 4;
constexpr int kPartStride = 20, kPartOdd = (kFW / 2) * kPartStride + 16, kPartSize = 2 * kPartOdd;
constexpr int kOffPart = kOffFin + kFW * 4;
constexpr int kOffMisc = kOffBar + (4 * kNS + 6 + kF * kFBoxes) * 8;
constexpr int kOffMax = kOffMisc + 32;
constexpr int kSmemBytes = kOffMax + 4 * kCW * 4;
constexpr int kRecWords = kD / 2;
constexpr int kHeadWords = kSlots * (kRecWords + 1);
constexpr int kPreWords = 112;
constexpr int kMG = 6;
static_assert(kNS >= 3, "ring");
static_assert(kOffBar % 8 == 0 && kOffSc % 16 == 0 && kOffMax % 16 == 0, "alignment");
static_assert(kPR % kMG == 0, "ring");
static_assert(kOffMisc % 16 == 0 && kLeadEnd - (kFBoxes / 2 - 1) * kBoxStep >= kStream && kS == kFHeads * kFRows && kFHeads == 8, "schedule");
static_assert(kSmemBytes <= 232448, "smem");
static_assert(kDef0 + kFHeads < kPrep && kPrep + 16 + 3 < kRounds && kEarly + kF * kFBoxes + 3 < kRounds && kOffPart <= kOffScal + (kPrep - 2) * 4 * kRows * 2 &&
              kOffPart + kF * kPartSize * 4 <= kOffScal + (kRounds - 2) * 4 * kRows * 2 && kF <= kNS && kFBoxes == kCW, "deferred rounds");

__device__ __align__(128) unsigned long long g_rec[kPR * kTeams * kHeadWords];
__device__ __align__(128) unsigned long long g_pre[kTeams * kFHeads * kPreWords];
__device__ __align__(128) unsigned long long g_lg[kTeams * kFHeads * kF * kFRows];
__device__ unsigned int g_prog[(16384 + 8192) / 4 + 1];
__device__ __align__(128) unsigned int g_epoch;
__device__ __align__(128) unsigned int g_arrive;
__device__ __align__(128) unsigned int g_mdone[kTeams * kMG * 32];

constexpr int kSpin = 1 << 24;

__device__ __forceinline__ uint32_t clock32() {
    uint32_t t;
    asm volatile("mov.u32 %0, %%clock;" : "=r"(t)::"memory");
    return t;
}
__device__ __forceinline__ unsigned int* prog_counter(int j) {
    return reinterpret_cast<unsigned int*>(((reinterpret_cast<uintptr_t>(g_prog) + 16383) & ~(uintptr_t)16383) + 8192 * j);
}
__device__ __forceinline__ uint32_t s2u(const void* p) { return (uint32_t)__cvta_generic_to_shared(p); }
__device__ __forceinline__ void mbar_init(uint32_t a, int c) {
    asm volatile("mbarrier.init.shared::cta.b64 [%0], %1;" ::"r"(a), "r"(c));
}
__device__ __forceinline__ void mbar_wait(uint32_t a, uint32_t ph) {
    uint32_t ok;
    for (int it = 0;; it++) {
        asm volatile(
            "{\n.reg .pred p;\nmbarrier.try_wait.parity.shared::cta.b64 p, [%1], %2;\nselp.u32 %0, 1, 0, p;\n}"
            : "=r"(ok) : "r"(a), "r"(ph) : "memory");
        if (ok) break;
        if (it > kSpin) __trap();
    }
}
__device__ __forceinline__ void mbar_arrive(uint32_t a) {
    asm volatile("mbarrier.arrive.shared::cta.b64 _, [%0];" ::"r"(a) : "memory");
}
__device__ __forceinline__ void mbar_expect(uint32_t a, uint32_t bytes) {
    asm volatile("mbarrier.arrive.expect_tx.shared::cta.b64 _, [%0], %1;" ::"r"(a), "r"(bytes) : "memory");
}
__device__ __forceinline__ void bulk_g2s_stream(uint32_t dst, const void* src, uint32_t bytes, uint32_t mbar, uint64_t pol) {
    asm volatile("cp.async.bulk.shared::cluster.global.mbarrier::complete_tx::bytes.L2::cache_hint [%0], [%1], %2, [%3], %4;"
                 ::"r"(dst), "l"(src), "r"(bytes), "r"(mbar), "l"(pol) : "memory");
}
__device__ __forceinline__ void bulk_g2s(uint32_t dst, const void* src, uint32_t bytes, uint32_t mbar) {
    asm volatile("cp.async.bulk.shared::cluster.global.mbarrier::complete_tx::bytes [%0], [%1], %2, [%3];"
                 ::"r"(dst), "l"(src), "r"(bytes), "r"(mbar) : "memory");
}
__device__ __forceinline__ void cp16(uint32_t dst, const void* src) {
    asm volatile("cp.async.cg.shared.global [%0], [%1], 16;" ::"r"(dst), "l"(src) : "memory");
}
__device__ __forceinline__ float bf_lo(uint32_t u) { return __uint_as_float(u << 16); }
__device__ __forceinline__ float bf_hi(uint32_t u) { return __uint_as_float(u & 0xffff0000u); }
__device__ __forceinline__ float bf_round(float x) { return __bfloat162float(__float2bfloat16_rn(x)); }
__device__ __forceinline__ uint32_t ld_pair(const __nv_bfloat16* p) {
    return __ldg(reinterpret_cast<const uint32_t*>(p));
}
__device__ __forceinline__ unsigned int ld_relaxed(const unsigned int* p) {
    unsigned int v;
    asm volatile("ld.relaxed.gpu.global.u32 %0, [%1];" : "=r"(v) : "l"(p) : "memory");
    return v;
}
__device__ __forceinline__ unsigned long long pack_rec(float a, float b, uint32_t tag) {
    const uint32_t x = (__float_as_uint(a) & ~15u) | (tag & 15u), y = (__float_as_uint(b) & ~15u) | (tag >> 4);
    return ((unsigned long long)y << 32) | x;
}
__device__ __forceinline__ void st_rec(unsigned long long* p, float a, float b, uint32_t tag) {
    asm volatile("st.relaxed.gpu.global.b64 [%0], %1;" ::"l"(p), "l"(pack_rec(a, b, tag)) : "memory");
}
__device__ __forceinline__ float rec_lo(unsigned long long w) { return __uint_as_float((uint32_t)w & ~15u); }
__device__ __forceinline__ float rec_hi(unsigned long long w) { return __uint_as_float((uint32_t)(w >> 32) & ~15u); }
__device__ __forceinline__ unsigned long long ld_rec1(const unsigned long long* p) {
    unsigned long long x;
    asm volatile("ld.relaxed.gpu.global.b64 %0, [%1];" : "=l"(x) : "l"(p) : "memory");
    return x;
}
__device__ __forceinline__ void ld_rec2(const unsigned long long* p, unsigned long long& x, unsigned long long& y) {
    asm volatile("ld.relaxed.gpu.global.v2.b64 {%0, %1}, [%2];" : "=l"(x), "=l"(y) : "l"(p) : "memory");
}
__device__ __forceinline__ uint32_t rec_bad(unsigned long long w, uint32_t tlo, uint32_t thi) {
    return (((uint32_t)w ^ tlo) | ((uint32_t)(w >> 32) ^ thi)) & 15u;
}
__device__ __forceinline__ void st_ml(unsigned long long* p, float m, float l, uint32_t tag) {
    const uint32_t y = ((__float_as_uint(l) + 0x80u) & ~0xffu) | tag;
    asm volatile("st.relaxed.gpu.global.b64 [%0], %1;" ::"l"(p), "l"(((unsigned long long)y << 32) | __float_as_uint(m)) : "memory");
}
__device__ __forceinline__ uint32_t ml_bad(unsigned long long w, uint32_t tag) { return ((uint32_t)(w >> 32) ^ tag) & 0xffu; }
__device__ __forceinline__ float ml_m(unsigned long long w) { return __uint_as_float((uint32_t)w); }
__device__ __forceinline__ float ml_l(unsigned long long w) { return __uint_as_float((uint32_t)(w >> 32) & ~0xffu); }
__device__ __forceinline__ float warp_max(float v) {
    const int b = __float_as_int(v);
    const int k = __reduce_max_sync(0xffffffffu, b ^ ((b >> 31) & 0x7fffffff));
    return __int_as_float(k ^ ((k >> 31) & 0x7fffffff));
}
__device__ __forceinline__ uint32_t round_tag(unsigned int epoch, int r) {
    constexpr unsigned kUses = (kRounds + kPR - 1) / kPR;
    return (epoch * kUses + (unsigned)(r / kPR)) % 255u + 1u;
}

__device__ __forceinline__ void rotate_q(uint32_t* qrow, int p, uint32_t c_lo, uint32_t c_hi, uint32_t s_lo, uint32_t s_hi) {
    const uint32_t lo = qrow[p], hi = qrow[p + 48];
    const float a0 = bf_round(bf_lo(lo) * bf_lo(c_lo)) + bf_round(-bf_lo(hi) * bf_lo(s_lo));
    const float a1 = bf_round(bf_hi(lo) * bf_hi(c_lo)) + bf_round(-bf_hi(hi) * bf_hi(s_lo));
    const float b0 = bf_round(bf_lo(hi) * bf_lo(c_hi)) + bf_round(bf_lo(lo) * bf_lo(s_hi));
    const float b1 = bf_round(bf_hi(hi) * bf_hi(c_hi)) + bf_round(bf_hi(lo) * bf_hi(s_hi));
    const __nv_bfloat162 ua = __floats2bfloat162_rn(a0, a1), ub = __floats2bfloat162_rn(b0, b1);
    qrow[p] = *reinterpret_cast<const uint32_t*>(&ua);
    qrow[p + 48] = *reinterpret_cast<const uint32_t*>(&ub);
}
__device__ __forceinline__ int head_of(int team, int r) { return (team >> 1) * (kNH / 2) + 2 * r + (team & 1); }
__device__ __forceinline__ int deferred_to(int blk, int r) {
    return (unsigned)(r - kDef0) < (unsigned)kFHeads ? (blk - kF * (r - kDef0)) & (kFHeads - 1) : kF;
}

__device__ __forceinline__ unsigned role_of_sm(unsigned smid) {
    const unsigned u = smid >> 1;
    const unsigned g = u < 32 ? u & 7 : u < 60 ? 1 + (u - 32) % 7 : u < 62 ? u - 54 : 0;
    const unsigned t = u < 32 ? u >> 3 : u < 60 ? 4 + (u - 32) / 7 : u < 62 ? 8 : u - 58;
    const unsigned lin = 16 * g + (g == 7 ? 2 : 0) + 2 * t + (smid & 1);
    return lin < 2 ? lin + kStream : lin < 48 ? lin - 2 : lin < 50 ? lin + (kStream + 2 - 48) : lin - 4;
}
static_assert(kGrid == 132 && kTeams == 4, "role_of_sm");
struct Scalars { const __nv_bfloat16* p[4]; };

__global__ void __launch_bounds__(kThreads, 1)
attn_kernel(const __grid_constant__ Scalars scal, const int* __restrict__ qk, int by_sm, const __nv_bfloat16* __restrict__ kcos,
            const __nv_bfloat16* __restrict__ ksin, const int* __restrict__ qv, const __nv_bfloat16* __restrict__ q,
            const __nv_bfloat16* __restrict__ qcos, const __nv_bfloat16* __restrict__ qsin,
            __nv_bfloat16* __restrict__ out, const __grid_constant__ CUtensorMap tmv) {
    extern __shared__ __align__(128) unsigned char smem[];
    const int warp = threadIdx.x >> 5, lane = threadIdx.x & 31;
    const uint32_t full0 = s2u(smem + kOffBar), empty0 = full0 + 2 * kNS * 8;
    const uint32_t sfull = empty0 + 2 * kNS * 8, sempty = sfull + 16, mxbar = sempty + 16, fine = mxbar + 16;
    volatile unsigned int* s_misc = reinterpret_cast<volatile unsigned int*>(smem + kOffMisc);
    uint64_t pol = 0;

    asm volatile("prefetch.global.L2 [%0];"
                 ::"l"(reinterpret_cast<const char*>(qk) + (blockIdx.x * (kThreads / 4) + threadIdx.x / 4) * 128) : "memory");
    unsigned bid = blockIdx.x;
    if (by_sm) {
        unsigned smid, nsm;
        asm volatile("mov.u32 %0, %%smid;" : "=r"(smid));
        asm volatile("mov.u32 %0, %%nsmid;" : "=r"(nsm));
        if (nsm == kGrid) bid = role_of_sm(smid);
    }
    if (bid < kStream) bid = (bid & 14) * 8 + (bid >> 4) * 2 + (bid & 1);
    if (threadIdx.x == kCW * 32 && bid < kStream) {
        const int m = bid % kSlots;
        const uint32_t sm0 = s2u(smem);
        asm volatile("cp.async.bulk.prefetch.L2.global [%0], %1;"
                     ::"l"(scal.p[bid & 3] + (bid >> 2) * (kNH * kS * 4 / kStream)), "n"(kNH * kS * 4 / kStream * 2) : "memory");
        for (int i = 0; i < 2 * kNS; i++) mbar_init(full0 + 8 * i, 1);
        asm volatile("fence.mbarrier_init.release.cluster;" ::: "memory");
        asm volatile("createpolicy.fractional.L2::evict_first.b64 %0, 1.0;" : "=l"(pol));
        const int* k0 = qk + (size_t)(head_of(bid / kSlots, 0) * kS + m * kHRows) * kD;
#pragma unroll
        for (int h = 0; h < 2; h++) {
            mbar_expect(full0 + 16 + 8 * h, kHalf);
            bulk_g2s_stream(sm0 + kChunk + h * kHalf, k0 + h * (kS / 2 * kD), kHalf, full0 + 16 + 8 * h, pol);
        }
#pragma unroll
        for (int h = 0; h < 2; h++) {
            mbar_expect(full0 + 8 * h, kHalf);
            bulk_g2s(sm0 + h * kHalf, kcos + (h * (kS / 2) + m * kHRows) * kD, kHalf / 2, full0 + 8 * h);
            bulk_g2s(sm0 + h * kHalf + kHalf / 2, ksin + (h * (kS / 2) + m * kHRows) * kD, kHalf / 2, full0 + 8 * h);
        }
#pragma unroll
        for (int h = 0; h < 2; h++) {
            mbar_expect(full0 + 32 + 8 * h, kHalf);
            bulk_g2s_stream(sm0 + 2 * kChunk + h * kHalf, k0 + (2 * kS + h * (kS / 2)) * kD, kHalf, full0 + 32 + 8 * h, pol);
        }
    }

    if (bid >= kStream) {
        const int team = bid - kStream;
        if (threadIdx.x == 0) s_misc[0] = ld_relaxed(&g_epoch);
        __syncthreads();
        if (threadIdx.x == 0 && atomicAdd(&g_arrive, 1u) == kGrid - 1) { g_arrive = 0u; g_epoch = s_misc[0] + 1u; }
        if (warp >= 3 * kMG) return;
        const int grp = warp / 3, t = threadIdx.x - grp * 96;
        constexpr int kRecBytes = kHeadWords * 8;
        if (t == 0) {
            mbar_init(s2u(smem + kOffBar) + grp * 8, 1);
            asm volatile("fence.mbarrier_init.release.cluster;" ::: "memory");
        }
        asm volatile("bar.sync %0, 96;" ::"r"(3 + grp) : "memory");
        for (int r = grp; r < kRounds; r += kMG) {
            const int g = r % kMG;
            const int tt = threadIdx.x - g * 96, qd = tt % 48, half = tt / 48;
            const uint32_t tag = round_tag(s_misc[0], r);
            const uint32_t tlo = tag & 15u, thi = tag >> 4;
            const unsigned long long* rec = g_rec + (size_t)(r % kPR * kTeams + team) * kHeadWords;
            unsigned long long ml, x[16], y[16];
            {
                const unsigned long long* buf = reinterpret_cast<const unsigned long long*>(smem + g * kRecBytes);
                const uint32_t mb = s2u(smem + kOffBar) + g * 8;
                if (tt < 32) {
                    const int want = r == kRounds - 1 ? kQuick : kSlots;
                    for (int i2 = 0;; i2++) {
                        ml = ld_rec1(rec + kSlots * kRecWords + lane);
                        if (__popc(__ballot_sync(0xffffffffu, ml_bad(ml, tag) == 0)) >= want) break;
                        if (i2 > kSpin) __trap();
                        __nanosleep(r >= kRounds - 2 ? kSleep : 5 * kSleep);
                    }
                    if (tt == 0) {
                        mbar_expect(mb, kRecBytes);
                        bulk_g2s(s2u(buf), rec, kRecBytes, mb);
                    }
                }
                mbar_wait(mb, (r / kMG) & 1);
                ml = buf[kSlots * kRecWords + lane];
#pragma unroll
                for (int i = 0; i < 16; i++) {
                    const ulonglong2 u = *reinterpret_cast<const ulonglong2*>(buf + (half * 16 + i) * kRecWords + 2 * qd);
                    x[i] = u.x; y[i] = u.y;
                }
                const unsigned long long* po = rec + half * 16 * kRecWords + 2 * qd;
                for (int it = 0;; it++) {
                    uint32_t any = ml_bad(ml, tag);
                    if (any) ml = ld_rec1(rec + kSlots * kRecWords + lane);
#pragma unroll
                    for (int i = 0; i < 16; i++) {
                        const uint32_t bad = rec_bad(x[i], tlo, thi) | rec_bad(y[i], tlo, thi);
                        if (bad) ld_rec2(po + i * kRecWords, x[i], y[i]);
                        any |= bad;
                    }
                    if (__all_sync(0xffffffffu, any == 0)) break;
                    if (it > kSpin) __trap();
                }
            }
            const float M = ml_m(ml);
            const float MM = warp_max(M);
            const float w = exp2f(M - MM);
            float LL = w * ml_l(ml);
#pragma unroll
            for (int o = 16; o > 0; o >>= 1) LL += __shfl_xor_sync(0xffffffffu, LL, o);
            float4 a = make_float4(0.f, 0.f, 0.f, 0.f);
#pragma unroll
            for (int i = 0; i < 16; i++) {
                const float wi = __shfl_sync(0xffffffffu, w, half * 16 + i);
                a.x = fmaf(wi, rec_lo(x[i]), a.x);
                a.y = fmaf(wi, rec_hi(x[i]), a.y);
                a.z = fmaf(wi, rec_lo(y[i]), a.z);
                a.w = fmaf(wi, rec_hi(y[i]), a.w);
            }
            float* rb = reinterpret_cast<float*>(smem + kMG * kRecBytes) + (2 * g + ((r / kMG) & 1)) * kD + 4 * qd;
            if (half == 1) *reinterpret_cast<float4*>(rb) = a;
            asm volatile("bar.sync %0, 96;" ::"r"(3 + g) : "memory");
            if (half == 0) {
                const float4 u = *reinterpret_cast<float4*>(rb);
                if ((unsigned)(r - kDef0) < (unsigned)kFHeads) {
                    unsigned long long* pre = g_pre + (size_t)(team * kFHeads + r - kDef0) * kPreWords;
                    const uint32_t ptag = s_misc[0] % 255u + 1u;
                    st_rec(pre + 2 * qd, a.x + u.x, a.y + u.y, ptag);
                    st_rec(pre + 2 * qd + 1, a.z + u.z, a.w + u.w, ptag);
                    if (qd == 0) st_ml(pre + 96, MM, LL, ptag);
                } else {
                    const float inv = __fdividef(1.0f, LL);
                    const __nv_bfloat162 o0 = __floats2bfloat162_rn((a.x + u.x) * inv, (a.y + u.y) * inv);
                    const __nv_bfloat162 o1 = __floats2bfloat162_rn((a.z + u.z) * inv, (a.w + u.w) * inv);
                    uint2 ov;
                    ov.x = *reinterpret_cast<const uint32_t*>(&o0);
                    ov.y = *reinterpret_cast<const uint32_t*>(&o1);
                    *reinterpret_cast<uint2*>(out + (size_t)head_of(team, r) * kD + 4 * qd) = ov;
                }
            }
            if (tt == 95)
                asm volatile("st.relaxed.gpu.global.u32 [%0], %1;" ::"l"(&g_mdone[(team * kMG + g) * 32]), "r"(s_misc[0] * kRounds + r + 1) : "memory");
        }
        return;
    }

    const int m = bid % kSlots, team = bid / kSlots;
    const int row0 = m * kHRows;

    if (warp == kCW || warp == kCW + 3) {
        const int h = warp != kCW;
        const uint32_t sm0 = s2u(smem);
        if (threadIdx.x == kCW * 32) {
            const unsigned int epoch = ld_relaxed(&g_epoch);
            s_misc[0] = epoch;
            s_misc[1] = s_misc[2] = 0;
            s_misc[4] = epoch * (kStream * (4 * kRounds - 2));
            s_misc[5] = clock32();
        }
        __syncwarp();
        asm volatile("bar.sync 2, %0;" ::"n"(kThreads) : "memory");
        if (lane < kFBoxes / 2) {
            constexpr unsigned kMask = (1u << (kFBoxes / 2)) - 1;
            const int box = h * (kFBoxes / 2) + lane;
            asm volatile("createpolicy.fractional.L2::evict_first.b64 %0, 1.0;" : "=l"(pol));
            const unsigned int base = s_misc[0] * (kStream * (4 * kRounds - 2));
            const int phase = (team & 1 ? kStream : -kStream) + (2 * m + 1 - kSlots) * (kWaveSlot / 2) + (team & 2 ? kWaveG : -kWaveG);
            int u = kNS;
            for (int p = 2; p < 2 * kRounds + kF; p++) {
                const int pos = 2 * p + h;
                const bool fin = p >= 2 * kRounds;
                const bool isv = (p & 1) == 0 || p == 2 * kRounds - 1;
                const int r = p == 2 * kRounds - 1 ? kRounds - 1 : isv ? (p >> 1) - 1 : (p + 1) >> 1;
                if (isv && deferred_to(4 * h + m / 8, r) < kF) continue;
                const int piece = (head_of(team, r) * 2 + h) * kSlots + m;
                const int ramp = max(min(min(2 * (pos - 4), 4 * kRounds - pos), kWaveRamp), 0);
                const int inblk = (3 * piece + 1 + kBlock8 - (isv ? kOriginV : kOriginK)) % kBlock8;
                const int tau = kStream * pos + (phase + (isv ? kWaveV : -kWaveV) + (kBlock8 / 2 - inblk) * 4 / 3) * ramp / kWaveRamp;
                const int gone = min(max(tau - kStream * (4 * kDef0 + 3), 0), 4 * kStream * kFHeads) * kF / (2 * kFHeads);
                const unsigned int need = base + tau - gone - max(kRampEnd - pos, 0) * kRampStep - (fin ? kLeadEnd - lane * kBoxStep : kLead);
                const int slot = u >= kNS ? u - kNS : u;
                const uint32_t dst = sm0 + slot * kChunk + box * (kChunk / kFBoxes), fullb = full0 + 16 * slot + 8 * h;
                const int* src = (isv ? qv : qk) + (size_t)piece * (kHRows * kD);
                const int row = head_of(team, kDef0 + m / kFG) * kS + ((kF * (m / kFG) + p - 2 * kRounds) & (kFHeads - 1)) * kFRows +
                                box * (kFRows / kFBoxes);
                const uint32_t fb = fine + 8 * (kFBoxes * (p - 2 * kRounds) + box);
                mbar_wait(fullb + 2 * kNS * 8, u >= kNS ? 0 : 1);
                u = u + 1 == 2 * kNS ? 0 : u + 1;
                if (!fin && lane == 0) mbar_expect(fullb, kHalf);
                bool todo = fin || lane == 0;
                for (int it = 0; __any_sync(kMask, todo); it++) {
                    uint32_t x, tx;
                    asm volatile("ld.volatile.shared.v2.u32 {%0, %1}, [%2];" : "=r"(x), "=r"(tx) : "r"(sm0 + kOffMisc + 16) : "memory");
                    x += min(((clock32() - tx) * kRate) >> 10, kAhead);
                    const bool go = todo && (int)(x - need) >= 0;
                    if (it > 16 * kSpin) __trap();
                    if (!__any_sync(kMask, go)) continue;
                    asm volatile("{\n.reg .pred p, q;\nsetp.ne.u32 p, %9, 0;\nsetp.ne.u32 q, %10, 0;\n"
                                 "@p cp.async.bulk.shared::cluster.global.mbarrier::complete_tx::bytes.L2::cache_hint [%0], [%1], %2, [%3], %4;\n"
                                 "@q cp.async.bulk.tensor.2d.shared::cluster.global.tile.mbarrier::complete_tx::bytes.L2::cache_hint [%0], [%5, {%6, %7}], [%8], %4;\n}"
                                 ::"r"(dst), "l"(src), "n"(kHalf), "r"(fullb), "l"(pol), "l"(&tmv), "r"((m % kFG) * kFW), "r"(row), "r"(fb),
                                   "r"((uint32_t)(go && !fin)), "r"((uint32_t)(go && fin)) : "memory");
                    todo = todo && !go;
                }
            }
            if (lane == 0) s_misc[1 + h] = 1;
        }
    } else if (warp == kCW + 2) {
        asm volatile("bar.sync 2, %0;" ::"n"(kThreads) : "memory");
        if (lane == 0) {
            const uint32_t dst = s2u(smem) + kOffMisc + 16;
            uint32_t ve = s_misc[4] << 4, te = s_misc[5];
            for (int it = 0; !(s_misc[1] & s_misc[2]); it++) {
                const uint32_t t = clock32();
                const uint32_t v = ld_relaxed(prog_counter((it ^ m) & 1));
                const uint32_t pred = ve + (min(t - te, 1u << 16) * kRate >> 6);
                const int err = (int)((v << 4) - pred);
                ve = pred + (abs(err) > kJump * 16 ? err : err >> kSmooth);
                te = t;
                asm volatile("st.volatile.shared.v2.u32 [%0], {%1, %2};" ::"r"(dst), "r"(v - ((int)((v << 4) - ve) >> 4)), "r"(te) : "memory");
                if (it > kSpin) __trap();
                __nanosleep(kPollSleep);
            }
        }
    } else if (warp == kCW + 1) {
        {
            if (lane < 2 * kNS + 6) mbar_init(empty0 + 8 * lane, lane < 2 * kNS ? kCW / 2 : (lane >= 2 * kNS + 2 && lane < 2 * kNS + 4) ? 1 : kCW);
            asm volatile("fence.mbarrier_init.release.cluster;" ::: "memory");
        }
        asm volatile("bar.sync 2, %0;" ::"n"(kThreads) : "memory");
        const unsigned int epoch = s_misc[0];
        if (lane == 0 && atomicAdd(&g_arrive, 1u) == kGrid - 1) { g_arrive = 0u; g_epoch = epoch + 1u; }
        {
            const uint32_t sm0 = s2u(smem);
            const __nv_bfloat16* src = scal.p[lane >> 3] + (size_t)head_of(team, 0) * kS + row0 + (lane & 4) * (kS / 8) + (lane & 3) * 8;
            const __nv_bfloat16* qs = q + head_of(team, 0) * kD + lane * 8;
#pragma unroll 1
            for (int r = kEarly; r < kRounds; r++) {
                cp16(sm0 + kOffScal + r * 512 + lane * 16, src + (size_t)r * (2 * kS));
                if (lane < 24) cp16(sm0 + kOffQ + r * (kD * 2) + lane * 16, qs + r * (2 * kD));
                if (r == 2 * kEarly - 1 || r == kRounds - 1) asm volatile("cp.async.commit_group;" ::: "memory");
            }
        }
        uint32_t cs[2][4];
#pragma unroll
        for (int i = 0; i < 2; i++) {
            const int p = (lane + 32 * i) % 48;
            cs[i][0] = ld_pair(qcos + 2 * p); cs[i][1] = ld_pair(qcos + 2 * p + 96);
            cs[i][2] = ld_pair(qsin + 2 * p); cs[i][3] = ld_pair(qsin + 2 * p + 96);
        }
        asm volatile("cp.async.wait_group 1;" ::: "memory");
        __syncwarp();
        for (int r = 0; r < kRounds; r++) {
            const float* sc = reinterpret_cast<const float*>(smem + kOffSc) + (r & 1) * (kCW * kScStride);
            const uint32_t tag = round_tag(epoch, r);
            unsigned long long* rec = g_rec + (size_t)(r % kPR * kTeams + team) * kHeadWords;
            if (r >= kEarly && r < kEarly + kF * kFBoxes && lane == 0) {
                mbar_init(fine + 8 * (r - kEarly), 1);
                asm volatile("fence.mbarrier_init.release.cluster;" ::: "memory");
                mbar_expect(fine + 8 * (r - kEarly), kChunk / kFBoxes);
                asm volatile("fence.proxy.async.shared::cta;" ::: "memory");
            }
            if (r == kPrep + m / 2) {
                const unsigned long long* pre = g_pre + (size_t)(team * kFHeads + m / kFG) * kPreWords;
                const unsigned long long* lgp = g_lg + (size_t)(team * kFHeads + m / kFG) * (kF * kFRows);
                const uint32_t ptag = epoch % 255u + 1u;
                unsigned long long ml, po;
                for (int it = 0;; it++) {
                    ml = ld_rec1(pre + 96);
                    po = ld_rec1(pre + (m % kFG) * (kFW / 2) + lane % (kFW / 2));
                    if (!(ml_bad(ml, ptag) | rec_bad(po, ptag & 15u, ptag >> 4))) break;
                    if (it > kSpin) __trap();
                }
                const float inv = 1.0f / ml_l(ml);
                if (lane < kFW / 2) {
                    reinterpret_cast<float2*>(smem + kOffFin)[lane] = make_float2(rec_lo(po) * inv, rec_hi(po) * inv);
                }
#pragma unroll 1
                for (int c = 0; c < kF; c++) {
                    unsigned long long u[8];
                    for (int it = 0;; it++) {
                        uint32_t bad = 0;
#pragma unroll
                        for (int k = 0; k < 8; k++) {
                            u[k] = ld_rec1(lgp + c * kFRows + 32 * k + lane);
                            bad |= ml_bad(u[k], ptag);
                        }
                        if (!bad) break;
                        if (it > kSpin) __trap();
                    }
#pragma unroll
                    for (int k = 0; k < 8; k++)
                        reinterpret_cast<float*>(smem + kOffW)[c * kFRows + 32 * k + lane] = ml_l(u[k]) * exp2f(ml_m(u[k]) - ml_m(ml)) * inv;
                }
                __syncwarp();
            }
            if (r == kRounds - 3 && lane == 0) asm volatile("prefetch.tensormap [%0];" ::"l"(&tmv) : "memory");
            if (r == kEarly) {
                asm volatile("cp.async.wait_all;" ::: "memory");
                __syncwarp();
            }
            if (r + kEarly < kRounds) {
                uint32_t* qrow = reinterpret_cast<uint32_t*>(smem + kOffQ + (r + kEarly) * (kD * 2));
                rotate_q(qrow, lane, cs[0][0], cs[0][1], cs[0][2], cs[0][3]);
                if (lane < 16) rotate_q(qrow, lane + 32, cs[1][0], cs[1][1], cs[1][2], cs[1][3]);
            }
            if (r >= kPR) {
                const unsigned int* mdone = &g_mdone[(team * kMG + r % kMG) * 32];
                const unsigned int need = epoch * kRounds + r - kPR + 1;
                for (int it = 0; (int)(ld_relaxed(mdone) - need) < 0; it++)
                    if (it > kSpin) __trap();
            }
            mbar_wait(sfull + 8 * (r & 1), (r >> 1) & 1);
            const float M = sc[0];
            float L = lane < kCW ? sc[lane * kScStride + 1] : 0.f;
            float acc[2][6];
#pragma unroll
            for (int ww = 0; ww < kCW; ww++) {
#pragma unroll
                for (int j = 0; j < 3; j++) {
                    const float2 t = *reinterpret_cast<const float2*>(sc + ww * kScStride + 4 + 64 * j + 2 * lane);
                    acc[ww & 1][2 * j] = ww < 2 ? t.x : acc[ww & 1][2 * j] + t.x;
                    acc[ww & 1][2 * j + 1] = ww < 2 ? t.y : acc[ww & 1][2 * j + 1] + t.y;
                }
                if ((ww & 3) == 3 && ww < 15) L += __shfl_xor_sync(0xffffffffu, L, 8 >> (ww >> 2));
            }
            L += __shfl_xor_sync(0xffffffffu, L, 1);
#pragma unroll
            for (int j = 0; j < 3; j++)
                st_rec(rec + m * kRecWords + 32 * j + lane, acc[0][2 * j] + acc[1][2 * j], acc[0][2 * j + 1] + acc[1][2 * j + 1], tag);
            if (lane == 0) st_ml(rec + kSlots * kRecWords + m, M, L, tag);
            __syncwarp();
            if (lane == 0) mbar_arrive(sempty + 8 * (r & 1));
        }
    } else {
        int dp[3];
#pragma unroll
        for (int j = 0; j < 3; j++) dp[j] = (64 * j + 2 * lane + 96) % kD;
        {
            const uint32_t sm0 = s2u(smem);
            if (warp < kEarly) {
                cp16(sm0 + kOffScal + threadIdx.x * 16, scal.p[lane >> 3] + (size_t)head_of(team, warp) * kS + row0 + (lane & 4) * (kS / 8) + (lane & 3) * 8);
            } else if (warp < 2 * kEarly && lane < 24) {
                cp16(sm0 + kOffQ + (warp - kEarly) * (kD * 2) + lane * 16, q + (size_t)head_of(team, warp - kEarly) * kD + lane * 8);
            }
            asm volatile("cp.async.commit_group;" ::: "memory");
        }
        const int p = threadIdx.x % 48, g = threadIdx.x / 48;
        const uint32_t c_lo = ld_pair(qcos + 2 * p), c_hi = ld_pair(qcos + 2 * p + 96);
        const uint32_t s_lo = ld_pair(qsin + 2 * p), s_hi = ld_pair(qsin + 2 * p + 96);
        float kc[kR][6], ks[kR][6];
        asm volatile("bar.sync 2, %0;" ::"n"(kThreads) : "memory");
        unsigned int* prog = prog_counter(((m >> 1) ^ (m >> 4) ^ team) & 1);
        const int mute = (m & 1) * 256;
        const int half = warp / (kCW / 2);
        const uint32_t fullh = full0 + 8 * half, emptyh = empty0 + 8 * half;
        mbar_wait(fullh, 0);
#pragma unroll
        for (int i = 0; i < kR; i++) {
            const unsigned char* cb = smem + half * (kHalf / 2) + (warp * kR + i) * (kD * 2);
#pragma unroll
            for (int j = 0; j < 3; j++) {
                const uint32_t uc = *reinterpret_cast<const uint32_t*>(cb + 128 * j + 4 * lane);
                const uint32_t us = *reinterpret_cast<const uint32_t*>(cb + kHalf / 2 + 2 * dp[j]);
                kc[i][2 * j] = bf_lo(uc); kc[i][2 * j + 1] = bf_hi(uc);
                const float sg = (j == 0 || (j == 1 && lane < 16)) ? 1.f : -1.f;
                ks[i][2 * j] = sg * bf_lo(us); ks[i][2 * j + 1] = sg * bf_hi(us);
            }
        }
        __syncwarp();
        if (lane == 0) mbar_arrive(emptyh);
        asm volatile("cp.async.wait_group 0;" ::: "memory");
        asm volatile("bar.sync 1, %0;" ::"n"(kCW * 32) : "memory");
        if (g < kEarly) rotate_q(reinterpret_cast<uint32_t*>(smem + kOffQ + g * (kD * 2)), p, c_lo, c_hi, s_lo, s_hi);
        asm volatile("bar.sync 1, %0;" ::"n"(kCW * 32) : "memory");
        const float scale_log2e = 1.4426950408889634f * rsqrtf((float)kD);
        float* my0 = reinterpret_cast<float*>(smem + kOffSc) + warp * kScStride;

        float* s_max = reinterpret_cast<float*>(smem + kOffMax);
        int slot = 1;
        uint32_t ph = 0;
        float lgc[kR] = {0.f, 0.f, 0.f, 0.f};
        for (int it = 0; it <= kRounds; it++) {
            float lg[kR];
            if (it < kRounds) {
                float qa[6], qb[6];
#pragma unroll
                for (int j = 0; j < 3; j++) {
                    const uint32_t qo = *reinterpret_cast<const uint32_t*>(smem + kOffQ + it * (kD * 2) + 2 * (64 * j + 2 * lane));
                    const uint32_t qp = *reinterpret_cast<const uint32_t*>(smem + kOffQ + it * (kD * 2) + 2 * dp[j]);
                    qa[2 * j] = bf_lo(qo); qa[2 * j + 1] = bf_hi(qo);
                    qb[2 * j] = bf_lo(qp); qb[2 * j + 1] = bf_hi(qp);
                }
                const unsigned char* sp = smem + kOffScal + it * (4 * kRows * 2) + warp * (kR * 2);
                const uint2 uks = *reinterpret_cast<const uint2*>(sp);
                const uint2 ukz = *reinterpret_cast<const uint2*>(sp + kRows * 2);
                const float kz[4] = {bf_lo(ukz.x), bf_hi(ukz.x), bf_lo(ukz.y), bf_hi(ukz.y)};
                const float sk[4] = {bf_lo(uks.x), bf_hi(uks.x), bf_lo(uks.y), bf_hi(uks.y)};
                mbar_wait(fullh + 16 * slot, ph);
                if ((threadIdx.x & 255) == mute) asm volatile("red.relaxed.gpu.global.add.u32 [%0], %1;" ::"l"(prog), "n"(kSample) : "memory");
                const unsigned char* kb = smem + slot * kChunk + warp * (kR * kRowBytes) + lane * 8;
#pragma unroll
                for (int i = 0; i < kR; i++) {
                    float dot = 0.f;
#pragma unroll
                    for (int j = 0; j < 3; j++) {
                        const int2 kk = *reinterpret_cast<const int2*>(kb + i * kRowBytes + 256 * j);
                        const float e0 = qa[2 * j] * kc[i][2 * j] + qb[2 * j] * ks[i][2 * j];
                        const float e1 = qa[2 * j + 1] * kc[i][2 * j + 1] + qb[2 * j + 1] * ks[i][2 * j + 1];
                        dot = fmaf((float)kk.x - kz[i], e0, dot);
                        dot = fmaf((float)kk.y - kz[i], e1, dot);
                    }
                    lg[i] = dot;
                }
                __syncwarp();
                if (lane == 0) mbar_arrive(emptyh + 16 * slot);
                if (++slot == kNS) { slot = 0; ph ^= 1; }
#pragma unroll
                for (int o = 16; o > 0; o >>= 1) {
#pragma unroll
                    for (int i = 0; i < kR; i++) lg[i] += __shfl_xor_sync(0xffffffffu, lg[i], o);
                }
                float mw = -INFINITY;
#pragma unroll
                for (int i = 0; i < kR; i++) {
                    lg[i] = lg[i] * sk[i] * scale_log2e;
                    mw = fmaxf(mw, lg[i]);
                }
                if (lane == 0) {
                    s_max[(it & 3) * kCW + warp] = mw;
                    mbar_arrive(mxbar + 8 * (it & 1));
                }
            }
            if (it > 0) {
                const int r = it - 1;
                float* my = my0 + (r & 1) * (kCW * kScStride);
                const int df = deferred_to(4 * half + m / 8, r);
                const unsigned char* sp = smem + kOffScal + r * (4 * kRows * 2) + warp * (kR * 2);
                const uint2 uvs = *reinterpret_cast<const uint2*>(sp + 2 * kRows * 2);
                const uint2 uvz = *reinterpret_cast<const uint2*>(sp + 3 * kRows * 2);
                const float vz[4] = {bf_lo(uvz.x), bf_hi(uvz.x), bf_lo(uvz.y), bf_hi(uvz.y)};
                const float sv[4] = {bf_lo(uvs.x), bf_hi(uvs.x), bf_lo(uvs.y), bf_hi(uvs.y)};
                mbar_wait(mxbar + 8 * (r & 1), (r >> 1) & 1);
                float M;
                {
                    const float4* pm4 = reinterpret_cast<const float4*>(s_max + (r & 3) * kCW);
                    const float4 m0 = pm4[0], m1 = pm4[1], m2 = pm4[2], m3 = pm4[3];
                    M = fmaxf(fmaxf(fmaxf(fmaxf(m0.x, m0.y), fmaxf(m0.z, m0.w)), fmaxf(fmaxf(m1.x, m1.y), fmaxf(m1.z, m1.w))),
                              fmaxf(fmaxf(fmaxf(m2.x, m2.y), fmaxf(m2.z, m2.w)), fmaxf(fmaxf(m3.x, m3.y), fmaxf(m3.z, m3.w))));
                }
                float lw = 0.f, cz = 0.f, pv[kR];
#pragma unroll
                for (int i = 0; i < kR; i++) {
                    const float p = exp2f(lgc[i] - M);
                    lw += p;
                    pv[i] = p * sv[i];
                    cz = fmaf(pv[i], vz[i], cz);
                }
                mbar_wait(sempty + 8 * (r & 1), ((r >> 1) & 1) ^ 1);
                if (lane == 0) { my[0] = M; my[1] = lw; }
                float acc[6] = {-cz, -cz, -cz, -cz, -cz, -cz};
                if (df < kF) {
                    if (lane < kR)
                        st_ml(g_lg + ((team * kFHeads + r - kDef0) * kF + df) * kFRows + (m % 8) * kHRows + (warp % 8) * kR + lane, M,
                              lane == 0 ? pv[0] : lane == 1 ? pv[1] : lane == 2 ? pv[2] : pv[3], s_misc[0] % 255u + 1u);
                } else {
                    mbar_wait(fullh + 16 * slot, ph);
                    if ((threadIdx.x & 255) == mute) asm volatile("red.relaxed.gpu.global.add.u32 [%0], %1;" ::"l"(prog), "n"(kSample) : "memory");
                    const unsigned char* vb = smem + slot * kChunk + warp * (kR * kRowBytes) + lane * 8;
#pragma unroll
                    for (int i = 0; i < kR; i++) {
#pragma unroll
                        for (int j = 0; j < 3; j++) {
                            const int2 vv = *reinterpret_cast<const int2*>(vb + i * kRowBytes + 256 * j);
                            acc[2 * j] = fmaf(pv[i], (float)vv.x, acc[2 * j]);
                            acc[2 * j + 1] = fmaf(pv[i], (float)vv.y, acc[2 * j + 1]);
                        }
                    }
                    __syncwarp();
                    if (lane == 0) mbar_arrive(emptyh + 16 * slot);
                    if (++slot == kNS) { slot = 0; ph ^= 1; }
                }
#pragma unroll
                for (int j = 0; j < 3; j++)
                    *reinterpret_cast<float2*>(my + 4 + 64 * j + 2 * lane) = make_float2(acc[2 * j], acc[2 * j + 1]);
                __syncwarp();
                if (lane == 0) mbar_arrive(sfull + 8 * (r & 1));
            }
#pragma unroll
            for (int i = 0; i < kR; i++) lgc[i] = lg[i];
        }
        {
            const int cp = lane < kFW / 2 ? lane : 0;
            const int ft = threadIdx.x < kFW ? threadIdx.x : 0;
            const float fin = reinterpret_cast<const float*>(smem + kOffFin)[ft];
            __nv_bfloat16* op = out + (size_t)head_of(team, kDef0 + m / kFG) * kD + (m % kFG) * kFW + ft;
            float a0 = 0.f, a1 = 0.f, b0 = 0.f, b1 = 0.f;
#pragma unroll 1
            for (int f = 0; f < kF; f++) {
                const float* sw = reinterpret_cast<const float*>(smem + kOffW) + f * kFRows + (warp >> 2) * 16 + (warp & 3) * 4;
                const unsigned char* vb = smem + slot * kChunk + ((warp >> 2) * 16 + (warp & 3) * 4) * (kFW * 4) + cp * 8;
                const uint32_t fb = fine + (f * kFBoxes + (warp >> 2)) * 8;
                float* part = reinterpret_cast<float*>(smem + kOffPart) + f * kPartSize;
                float4 w[4];
#pragma unroll
                for (int k = 0; k < 4; k++) w[k] = *reinterpret_cast<const float4*>(sw + 64 * k);
#pragma unroll
                for (int k = 0; k < 4; k++) {
                    mbar_wait(fb + 32 * k, 0);
                    if ((k & 1) && threadIdx.x == kCW * 32 - 32 + mute && f < kF - 1) asm volatile("red.relaxed.gpu.global.add.u32 [%0], %1;" ::"l"(prog), "n"(kSample) : "memory");
                    const int2 v0 = *reinterpret_cast<const int2*>(vb + k * (64 * kFW * 4));
                    const int2 v1 = *reinterpret_cast<const int2*>(vb + k * (64 * kFW * 4) + kFW * 4);
                    const int2 v2 = *reinterpret_cast<const int2*>(vb + k * (64 * kFW * 4) + 2 * kFW * 4);
                    const int2 v3 = *reinterpret_cast<const int2*>(vb + k * (64 * kFW * 4) + 3 * kFW * 4);
                    a0 = fmaf(w[k].x, (float)v0.x, a0); a1 = fmaf(w[k].x, (float)v0.y, a1);
                    b0 = fmaf(w[k].y, (float)v1.x, b0); b1 = fmaf(w[k].y, (float)v1.y, b1);
                    a0 = fmaf(w[k].z, (float)v2.x, a0); a1 = fmaf(w[k].z, (float)v2.y, a1);
                    b0 = fmaf(w[k].w, (float)v3.x, b0); b1 = fmaf(w[k].w, (float)v3.y, b1);
                }
                if (lane < kFW / 2) {
                    part[lane * kPartStride + warp] = a0 + b0;
                    part[kPartOdd + lane * kPartStride + warp] = a1 + b1;
                }
                if (warp >= 2) {
                    asm volatile("bar.arrive %0, %1;" ::"r"(3 + f), "n"(kCW * 32) : "memory");
                } else {
                    asm volatile("bar.sync %0, %1;" ::"r"(3 + f), "n"(kCW * 32) : "memory");
                    const float4* ps = reinterpret_cast<const float4*>(part + (ft & 1) * kPartOdd + (ft >> 1) * kPartStride);
                    const float4 p0 = ps[0], p1 = ps[1], p2 = ps[2], p3 = ps[3];
                    const float sum = (((p0.x + p0.y) + (p0.z + p0.w)) + ((p1.x + p1.y) + (p1.z + p1.w))) +
                                      (((p2.x + p2.y) + (p2.z + p2.w)) + ((p3.x + p3.y) + ((p3.z + p3.w) + fin)));
                    asm volatile("{\n.reg .pred p;\n.reg .b16 h;\nsetp.ne.u32 p, %2, 0;\ncvt.rn.bf16.f32 h, %1;\n@p st.global.b16 [%0], h;\n}"
                                 ::"l"(op), "f"(sum), "r"((uint32_t)(f == kF - 1 && threadIdx.x < kFW)) : "memory");
                }
                if (++slot == kNS) slot = 0;
            }
        }
    }
}

__global__ void __launch_bounds__(256)
attn_fallback(const __nv_bfloat16* __restrict__ q, const int* __restrict__ qk,
              const __nv_bfloat16* __restrict__ ksc, const __nv_bfloat16* __restrict__ kzp,
              const int* __restrict__ qv, const __nv_bfloat16* __restrict__ vsc,
              const __nv_bfloat16* __restrict__ vzp, const __nv_bfloat16* __restrict__ qcos,
              const __nv_bfloat16* __restrict__ qsin, const __nv_bfloat16* __restrict__ kcos,
              const __nv_bfloat16* __restrict__ ksin, __nv_bfloat16* __restrict__ out) {
    __shared__ float qr[kD], lg[kS], red[8];
    const int h = blockIdx.x, t = threadIdx.x, warp = t >> 5, lane = t & 31;
    if (t < kD) {
        const float x = __bfloat162float(q[h * kD + t]);
        const float y = t < kD / 2 ? -__bfloat162float(q[h * kD + t + kD / 2]) : __bfloat162float(q[h * kD + t - kD / 2]);
        qr[t] = bf_round(bf_round(x * __bfloat162float(qcos[t])) + bf_round(y * __bfloat162float(qsin[t])));
    }
    __syncthreads();
    const float scale_log2e = 1.4426950408889634f * rsqrtf((float)kD);
    float mw = -INFINITY;
    for (int s = warp; s < kS; s += 8) {
        const size_t row = (size_t)h * kS + s;
        const float z = __bfloat162float(kzp[row]);
        float dot = 0.f;
        for (int d = lane; d < kD; d += 32) {
            const int dp = d < kD / 2 ? d + kD / 2 : d - kD / 2;
            const float sn = __bfloat162float(ksin[s * kD + dp]);
            const float e = qr[d] * __bfloat162float(kcos[s * kD + d]) + qr[dp] * (d < kD / 2 ? sn : -sn);
            dot = fmaf((float)qk[row * kD + d] - z, e, dot);
        }
        for (int o = 16; o > 0; o >>= 1) dot += __shfl_xor_sync(0xffffffffu, dot, o);
        dot = dot * __bfloat162float(ksc[row]) * scale_log2e;
        if (lane == 0) lg[s] = dot;
        mw = fmaxf(mw, dot);
    }
    if (lane == 0) red[warp] = mw;
    __syncthreads();
    float M = red[0];
    for (int i = 1; i < 8; i++) M = fmaxf(M, red[i]);
    __syncthreads();
    float l = 0.f;
    for (int s = t; s < kS; s += 256) { const float p = exp2f(lg[s] - M); l += p; lg[s] = p; }
    for (int o = 16; o > 0; o >>= 1) l += __shfl_xor_sync(0xffffffffu, l, o);
    if (lane == 0) red[warp] = l;
    __syncthreads();
    float L = 0.f;
    for (int i = 0; i < 8; i++) L += red[i];
    if (t < kD) {
        float acc = 0.f;
        for (int s = 0; s < kS; s++) {
            const size_t row = (size_t)h * kS + s;
            acc = fmaf(lg[s] * __bfloat162float(vsc[row]), (float)qv[row * kD + t] - __bfloat162float(vzp[row]), acc);
        }
        out[h * kD + t] = __float2bfloat16_rn(acc / L);
    }
}

}

extern "C" void kernel_launch(void* const* d_in, const int* in_sizes, int n_in, void* d_out, int out_size) {
    const __nv_bfloat16* q = (const __nv_bfloat16*)d_in[0];
    const int* qk = (const int*)d_in[1];
    const __nv_bfloat16* ksc = (const __nv_bfloat16*)d_in[2];
    const __nv_bfloat16* kzp = (const __nv_bfloat16*)d_in[3];
    const int* qv = (const int*)d_in[4];
    const __nv_bfloat16* vsc = (const __nv_bfloat16*)d_in[5];
    const __nv_bfloat16* vzp = (const __nv_bfloat16*)d_in[6];
    const __nv_bfloat16* qcos = (const __nv_bfloat16*)d_in[7];
    const __nv_bfloat16* qsin = (const __nv_bfloat16*)d_in[8];
    const __nv_bfloat16* kcos = (const __nv_bfloat16*)d_in[9];
    const __nv_bfloat16* ksin = (const __nv_bfloat16*)d_in[10];

    typedef CUresult (*EncodeFn)(CUtensorMap*, CUtensorMapDataType, cuuint32_t, void*, const cuuint64_t*, const cuuint64_t*,
                                 const cuuint32_t*, const cuuint32_t*, CUtensorMapInterleave, CUtensorMapSwizzle,
                                 CUtensorMapL2promotion, CUtensorMapFloatOOBfill);
    static EncodeFn encode = nullptr;
    static int by_sm = 0;
    static int mode = 0;
    if (!mode) {
        int dev = 0, sms = 0, occ = 0;
        cudaGetDevice(&dev);
        cudaDeviceGetAttribute(&sms, cudaDevAttrMultiProcessorCount, dev);
        cudaError_t e = cudaFuncSetAttribute(attn_kernel, cudaFuncAttributeMaxDynamicSharedMemorySize, kSmemBytes);
        if (e == cudaSuccess) e = cudaOccupancyMaxActiveBlocksPerMultiprocessor(&occ, attn_kernel, kThreads, kSmemBytes);
        void* fn = nullptr;
        cudaDriverEntryPointQueryResult qr;
        if (e == cudaSuccess) e = cudaGetDriverEntryPoint("cuTensorMapEncodeTiled", &fn, cudaEnableDefault, &qr);
        encode = (EncodeFn)fn;
        mode = (e == cudaSuccess && fn && occ * sms >= kGrid) ? 1 : 2;
        (void)cudaGetLastError();
        by_sm = sms == kGrid && occ == 1;
    }
    CUtensorMap tmv;
    bool fast = mode == 1;
    if (fast) {
        const cuuint64_t dims[2] = {(cuuint64_t)kD, (cuuint64_t)kNH * kS}, strides[1] = {(cuuint64_t)kRowBytes};
        const cuuint32_t box[2] = {(cuuint32_t)kFW, (cuuint32_t)(kFRows / kFBoxes)}, es[2] = {1, 1};
        fast = encode(&tmv, CU_TENSOR_MAP_DATA_TYPE_INT32, 2, (void*)qv, dims, strides, box, es, CU_TENSOR_MAP_INTERLEAVE_NONE,
                      CU_TENSOR_MAP_SWIZZLE_NONE, CU_TENSOR_MAP_L2_PROMOTION_L2_128B, CU_TENSOR_MAP_FLOAT_OOB_FILL_NONE) == CUDA_SUCCESS;
    }
    if (fast)
        attn_kernel<<<kGrid, kThreads, kSmemBytes>>>(Scalars{{ksc, kzp, vsc, vzp}}, qk, by_sm, kcos, ksin, qv, q, qcos, qsin,
                                                     (__nv_bfloat16*)d_out, tmv);
    else
        attn_fallback<<<kNH, 256>>>(q, qk, ksc, kzp, qv, vsc, vzp, qcos, qsin, kcos, ksin, (__nv_bfloat16*)d_out);
}
```
